```python
import torch

def _softmax(x, axis=-1):
    return torch.softmax(x, dim=axis)
def _gelu(x):
    return torch.nn.functional.gelu(x, approximate="tanh")
def _silu(x):
    return torch.nn.functional.silu(x)
def _sigmoid(x):
    return torch.sigmoid(x)
def _layernorm(x, axis=-1, eps=1e-5):
    m = x.mean(dim=axis, keepdim=True)
    v = x.var(dim=axis, keepdim=True, unbiased=False)
    return (x - m) / torch.sqrt(v + eps)
def _scatter_add(tgt, idx, src, axis=0):
    return tgt.clone().index_add_(axis, idx, src)
def _segment_sum(src, seg, n):
    out = torch.zeros((n,) + src.shape[1:], dtype=src.dtype)
    return out.index_add_(0, seg, src)
def _pad(x, pw):
    flat = tuple(v for pair in reversed(pw) for v in pair)
    return torch.nn.functional.pad(x, flat)

kernel_name = 'sequential_preLN__mha_block__geglu_ffn__prompt'

def setup_inputs():

    _w = (lambda a: (lambda t: t.to(torch.bfloat16) if t.is_floating_point() else t)(torch.as_tensor(a)))
    def _A_setup():
        B, S, D, H = 1, 2048, 640, 32
        return {
            "x": _w((lambda *s: torch.randn(*s, dtype=torch.bfloat16) * 0.05)(B, S, D)),
            "wqkv": _w((lambda *s: torch.randn(*s, dtype=torch.bfloat16) * 0.05)(D, 3 * D)),
            "wo": _w((lambda *s: torch.randn(*s, dtype=torch.bfloat16) * 0.05)(D, D)),
        }
    _A_in = _A_setup()

    def _B_setup():
        B, S, D, F = 1, 2048, 640, 1536
        return {
            "x": _w((lambda *s: torch.randn(*s, dtype=torch.bfloat16) * 0.05)(B, S, D)),
            "w_gate": _w((lambda *s: torch.randn(*s, dtype=torch.bfloat16) * 0.05)(D, F)),
            "w_up": _w((lambda *s: torch.randn(*s, dtype=torch.bfloat16) * 0.05)(D, F)),
            "w_down": _w((lambda *s: torch.randn(*s, dtype=torch.bfloat16) * 0.05)(F, D)),
        }
    _B_in = _B_setup()

    return {
        "A_x": _A_in["x"],
        "A_wqkv": _A_in["wqkv"],
        "A_wo": _A_in["wo"],
        "B_x": _B_in["x"],
        "B_w_gate": _B_in["w_gate"],
        "B_w_up": _B_in["w_up"],
        "B_w_down": _B_in["w_down"],
    }

def reference(A_x, A_wqkv, A_wo, B_x, B_w_gate, B_w_up, B_w_down):
    def _A_ref(x, wqkv, wo):
        B, S, D = x.shape
        H = 32
        Dh = D // H
        qkv = (lambda x, *d: x.permute(*d))((x @ wqkv).reshape(B, S, 3, H, Dh), 2, 0, 3, 1, 4)
        q, k, v = qkv[0], qkv[1], qkv[2]
        scores = torch.einsum("bhqd,bhkd->bhqk", q, k) * (Dh ** -0.5)
        p = _softmax(scores, axis=-1)
        o = torch.einsum("bhqk,bhkd->bhqd", p, v)
        return (lambda x, *d: x.permute(*d))(o, 0, 2, 1, 3).reshape(B, S, D) @ wo

    def _B_ref(x, w_gate, w_up, w_down):
        return (_gelu(x @ w_gate) * (x @ w_up)) @ w_down

    x = A_x
    h = x + _A_ref(_layernorm(x, axis=-1), A_wqkv, A_wo)
    h2 = h + _B_ref(_layernorm(h, axis=-1), B_w_gate, B_w_up, B_w_down)
    return h2
```

```cpp
#include <cuda_runtime.h>
#include <cuda_bf16.h>
#include <cuda.h>
#include <stdint.h>

typedef __nv_bfloat16 bf16;

constexpr int S_ = 2048, D_ = 640, H_ = 32, F_ = 1536;
constexpr int NCTA = 132, NTHR = 640;
#define INFL 3
constexpr uint32_t POLYMASK = 0x7777;

__device__ __align__(1024) uint8_t g_qkv[64 * 196608];
__device__ __align__(1024) uint8_t g_o[S_ * D_ * 2];
__device__ __align__(1024) bf16 g_h[S_ * D_];
__device__ __align__(1024) uint8_t g_act[S_ * F_ * 2];
__device__ __align__(128) uint2 g_stat1[S_];
__device__ __align__(128) float2 g_part2[S_ * 5];
__device__ __align__(128) float g_cs2[2 * F_];
__device__ __align__(128) float g_nrm[96 * 128];
enum { C_CS2 = 1, C_DONE = 2, C_EPOCH = 3, C_QKV = 4  , C_ATT = 36  , C_H = 52  , C_ACT = 78  , C_NUM = 110 };
__device__ __align__(128) uint32_t g_cnt[C_NUM * 32];

#define STAMP(i)
#define STAMPG(k)
#define TRACE(k, i)
enum { PH_PRE = 1, PH_QKV = 2, PH_ATT = 4, PH_OPJ = 8, PH_UP = 16, PH_DN = 32, PH_ALL = 63 };

struct Maps { CUtensorMap x, wqkv, wo, o, h, wg, wu, act, wd; };

constexpr uint32_t SM_RING = 163840;
constexpr uint32_t SM_CS = 229376;
constexpr uint32_t SM_BAR = SM_CS + 2560;
constexpr uint32_t SM_VER = SM_RING + 49152;
constexpr uint32_t SM_TOTAL = SM_BAR + 512;
enum { B_RF = 0  , B_RA = 8  , B_AF = 18  , B_TF = 26  , B_TURN = 34  , B_DEP1 = 37,
       B_DEP3 = 38, B_VER = 39, B_DEP4 = 40,
       B_TE = 41  , B_RE = 49  , B_FREE3 = 57, B_STG = 58, B_FREE0 = 59,
       B_STAT = 60  , B_STAT2 = 61  , B_FREE1 = 62, B_HALF1 = 63  , B_NUM = 64 };

__device__ __forceinline__ void wg_fence() { asm volatile("wgmma.fence.sync.aligned;" ::: "memory"); }
__device__ __forceinline__ void wg_commit() { asm volatile("wgmma.commit_group.sync.aligned;" ::: "memory"); }
template <int N> __device__ __forceinline__ void wg_wait() { asm volatile("wgmma.wait_group.sync.aligned %0;" ::"n"(N) : "memory"); }
template <int N> __device__ __forceinline__ void pin(float (&a)[N]) {
#pragma unroll
    for (int i = 0; i < N; i++) asm volatile("" : "+f"(a[i])::"memory");
}
template <int N> __device__ __forceinline__ void pin(uint32_t (&a)[N]) {
#pragma unroll
    for (int i = 0; i < N; i++) asm volatile("" : "+r"(a[i])::"memory");
}
__device__ __forceinline__ uint64_t mkdesc(uint32_t addr, uint32_t lbo, uint32_t sbo, uint32_t swz) {
    return (uint64_t)((addr & 0x3FFFF) >> 4) | ((uint64_t)(lbo >> 4) << 16) | ((uint64_t)(sbo >> 4) << 32) | ((uint64_t)swz << 62);
}
__device__ __forceinline__ void mbar_init(uint32_t bar, uint32_t cnt) { asm volatile("mbarrier.init.shared::cta.b64 [%0], %1;" ::"r"(bar), "r"(cnt) : "memory"); }
__device__ __forceinline__ void mbar_expect_tx(uint32_t bar, uint32_t bytes) { asm volatile("mbarrier.arrive.expect_tx.shared::cta.b64 _, [%0], %1;" ::"r"(bar), "r"(bytes) : "memory"); }
__device__ __forceinline__ void mbar_arrive(uint32_t bar) { asm volatile("mbarrier.arrive.shared::cta.b64 _, [%0];" ::"r"(bar) : "memory"); }
__device__ __forceinline__ void mbar_wait(uint32_t bar, uint32_t parity) {
    asm volatile("{\n.reg .pred p;\nW%=:\nmbarrier.try_wait.parity.shared::cta.b64 p, [%0], %1;\n@!p bra W%=;\n}\n" ::"r"(bar), "r"(parity) : "memory");
}
__device__ __forceinline__ void bulk_g2s(uint32_t dst, const void* src, uint32_t bytes, uint32_t bar) {
    asm volatile("cp.async.bulk.shared::cluster.global.mbarrier::complete_tx::bytes [%0], [%1], %2, [%3];" ::"r"(dst), "l"(src), "r"(bytes), "r"(bar) : "memory");
}
__device__ __forceinline__ void tma2d(uint32_t dst, const CUtensorMap* m, int c0, int c1, uint32_t bar) {
    asm volatile("cp.async.bulk.tensor.2d.shared::cluster.global.mbarrier::complete_tx::bytes [%0], [%1, {%3, %4}], [%2];" ::"r"(dst), "l"(m), "r"(bar), "r"(c0), "r"(c1) : "memory");
}
__device__ __forceinline__ void prefetch_map(const CUtensorMap* m) { asm volatile("prefetch.tensormap [%0];" ::"l"(m) : "memory"); }
__device__ __forceinline__ void l2_prefetch(const void* p, uint32_t bytes) { asm volatile("cp.async.bulk.prefetch.L2.global [%0], %1;" ::"l"(p), "r"(bytes) : "memory"); }
__device__ __forceinline__ void fence_async_global() { asm volatile("fence.proxy.async.global;" ::: "memory"); }
__device__ __forceinline__ void bar_sync(int id, int n) { asm volatile("bar.sync %0, %1;" ::"r"(id), "r"(n) : "memory"); }
__device__ __forceinline__ void publish(int pair) { asm volatile("bar.arrive %0, 288;" ::"r"(1 + pair) : "memory"); }
__device__ __forceinline__ void cnt_signal(int c) { asm volatile("red.release.gpu.global.add.u32 [%0], 1;" ::"l"(g_cnt + c * 32) : "memory"); }
__device__ __forceinline__ void cnt_wait(bool active, int c, uint32_t target) {
    if (active) {
        const uint32_t* p = g_cnt + c * 32;
#pragma unroll 1
        for (int it = 0; it < 1000000; it++) {
            uint32_t v;
            asm volatile("ld.acquire.gpu.global.u32 %0, [%1];" : "=r"(v) : "l"(p) : "memory");
            if ((int)(v - target) >= 0) break;
        }
    }
    __syncwarp();
}
__device__ __forceinline__ bool elect_one() {
    uint32_t p;
    asm volatile("{\n.reg .pred P;\nelect.sync _|P, 0xffffffff;\nselp.b32 %0, 1, 0, P;\n}\n" : "=r"(p));
    return p != 0;
}
__device__ __forceinline__ uint32_t pack_bf16(float lo, float hi) {
    uint32_t r;
    asm("cvt.rn.bf16x2.f32 %0, %1, %2;" : "=r"(r) : "f"(hi), "f"(lo));
    return r;
}
__device__ __forceinline__ float bf_lo(uint32_t v) { return __uint_as_float(v << 16); }
__device__ __forceinline__ float bf_hi(uint32_t v) { return __uint_as_float(v & 0xFFFF0000u); }
__device__ __forceinline__ float ex2(float x) {
    float r;
    asm("ex2.approx.ftz.f32 %0, %1;" : "=f"(r) : "f"(x));
    return r;
}

__device__ __forceinline__ void mma16816(float (&d)[4], const uint32_t (&a)[4], uint32_t b0, uint32_t b1) {
    asm volatile("mma.sync.aligned.m16n8k16.row.col.f32.bf16.bf16.f32 {%0, %1, %2, %3}, {%4, %5, %6, %7}, {%8, %9}, {%0, %1, %2, %3};"
                 : "+f"(d[0]), "+f"(d[1]), "+f"(d[2]), "+f"(d[3]) : "r"(a[0]), "r"(a[1]), "r"(a[2]), "r"(a[3]), "r"(b0), "r"(b1));
}

template <int SCALE_D>
__device__ __forceinline__ void wgmma_rs_n128(float (&d)[64], uint32_t a0, uint32_t a1, uint32_t a2, uint32_t a3, uint64_t db) {
    asm volatile(
        "wgmma.mma_async.sync.aligned.m64n128k16.f32.bf16.bf16 {"
        "%0, %1, %2, %3, %4, %5, %6, %7, %8, %9, %10, %11, %12, %13, %14, %15, "
        "%16, %17, %18, %19, %20, %21, %22, %23, %24, %25, %26, %27, %28, %29, %30, %31, "
        "%32, %33, %34, %35, %36, %37, %38, %39, %40, %41, %42, %43, %44, %45, %46, %47, "
        "%48, %49, %50, %51, %52, %53, %54, %55, %56, %57, %58, %59, %60, %61, %62, %63"
        "}, {%64, %65, %66, %67}, %68, %69, 1, 1, 0;\n"
        :
        "+f"(d[0]), "+f"(d[1]), "+f"(d[2]), "+f"(d[3]), "+f"(d[4]), "+f"(d[5]), "+f"(d[6]), "+f"(d[7]),
        "+f"(d[8]), "+f"(d[9]), "+f"(d[10]), "+f"(d[11]), "+f"(d[12]), "+f"(d[13]), "+f"(d[14]), "+f"(d[15]),
        "+f"(d[16]), "+f"(d[17]), "+f"(d[18]), "+f"(d[19]), "+f"(d[20]), "+f"(d[21]), "+f"(d[22]), "+f"(d[23]),
        "+f"(d[24]), "+f"(d[25]), "+f"(d[26]), "+f"(d[27]), "+f"(d[28]), "+f"(d[29]), "+f"(d[30]), "+f"(d[31]),
        "+f"(d[32]), "+f"(d[33]), "+f"(d[34]), "+f"(d[35]), "+f"(d[36]), "+f"(d[37]), "+f"(d[38]), "+f"(d[39]),
        "+f"(d[40]), "+f"(d[41]), "+f"(d[42]), "+f"(d[43]), "+f"(d[44]), "+f"(d[45]), "+f"(d[46]), "+f"(d[47]),
        "+f"(d[48]), "+f"(d[49]), "+f"(d[50]), "+f"(d[51]), "+f"(d[52]), "+f"(d[53]), "+f"(d[54]), "+f"(d[55]),
        "+f"(d[56]), "+f"(d[57]), "+f"(d[58]), "+f"(d[59]), "+f"(d[60]), "+f"(d[61]), "+f"(d[62]), "+f"(d[63])
        : "r"(a0), "r"(a1), "r"(a2), "r"(a3), "l"(db), "n"(SCALE_D));
}
template <int SCALE_D>
__device__ __forceinline__ void wgmma_rs_n24_tb(float (&d)[12], uint32_t a0, uint32_t a1, uint32_t a2, uint32_t a3, uint64_t db) {
    asm volatile(
        "wgmma.mma_async.sync.aligned.m64n24k16.f32.bf16.bf16 {"
        "%0, %1, %2, %3, %4, %5, %6, %7, %8, %9, %10, %11"
        "}, {%12, %13, %14, %15}, %16, %17, 1, 1, 1;\n"
        :
        "+f"(d[0]), "+f"(d[1]), "+f"(d[2]), "+f"(d[3]), "+f"(d[4]), "+f"(d[5]), "+f"(d[6]), "+f"(d[7]),
        "+f"(d[8]), "+f"(d[9]), "+f"(d[10]), "+f"(d[11])
        : "r"(a0), "r"(a1), "r"(a2), "r"(a3), "l"(db), "n"(SCALE_D));
}
__device__ __forceinline__ void wgmma_ss_n128_tb(float (&d)[64], uint64_t da, uint64_t db) {
    asm volatile(
        "wgmma.mma_async.sync.aligned.m64n128k16.f32.bf16.bf16 {"
        "%0, %1, %2, %3, %4, %5, %6, %7, %8, %9, %10, %11, %12, %13, %14, %15, "
        "%16, %17, %18, %19, %20, %21, %22, %23, %24, %25, %26, %27, %28, %29, %30, %31, "
        "%32, %33, %34, %35, %36, %37, %38, %39, %40, %41, %42, %43, %44, %45, %46, %47, "
        "%48, %49, %50, %51, %52, %53, %54, %55, %56, %57, %58, %59, %60, %61, %62, %63"
        "}, %64, %65, 1, 1, 1, 0, 1;\n"
        :
        "+f"(d[0]), "+f"(d[1]), "+f"(d[2]), "+f"(d[3]), "+f"(d[4]), "+f"(d[5]), "+f"(d[6]), "+f"(d[7]),
        "+f"(d[8]), "+f"(d[9]), "+f"(d[10]), "+f"(d[11]), "+f"(d[12]), "+f"(d[13]), "+f"(d[14]), "+f"(d[15]),
        "+f"(d[16]), "+f"(d[17]), "+f"(d[18]), "+f"(d[19]), "+f"(d[20]), "+f"(d[21]), "+f"(d[22]), "+f"(d[23]),
        "+f"(d[24]), "+f"(d[25]), "+f"(d[26]), "+f"(d[27]), "+f"(d[28]), "+f"(d[29]), "+f"(d[30]), "+f"(d[31]),
        "+f"(d[32]), "+f"(d[33]), "+f"(d[34]), "+f"(d[35]), "+f"(d[36]), "+f"(d[37]), "+f"(d[38]), "+f"(d[39]),
        "+f"(d[40]), "+f"(d[41]), "+f"(d[42]), "+f"(d[43]), "+f"(d[44]), "+f"(d[45]), "+f"(d[46]), "+f"(d[47]),
        "+f"(d[48]), "+f"(d[49]), "+f"(d[50]), "+f"(d[51]), "+f"(d[52]), "+f"(d[53]), "+f"(d[54]), "+f"(d[55]),
        "+f"(d[56]), "+f"(d[57]), "+f"(d[58]), "+f"(d[59]), "+f"(d[60]), "+f"(d[61]), "+f"(d[62]), "+f"(d[63])
        : "l"(da), "l"(db));
}
__device__ __forceinline__ void wgmma_ss_n80_ta(float (&d)[40], uint64_t da, uint64_t db) {
    asm volatile(
        "wgmma.mma_async.sync.aligned.m64n80k16.f32.bf16.bf16 {"
        "%0, %1, %2, %3, %4, %5, %6, %7, %8, %9, %10, %11, %12, %13, %14, %15, "
        "%16, %17, %18, %19, %20, %21, %22, %23, %24, %25, %26, %27, %28, %29, %30, %31, "
        "%32, %33, %34, %35, %36, %37, %38, %39"
        "}, %40, %41, 1, 1, 1, 1, 0;\n"
        :
        "+f"(d[0]), "+f"(d[1]), "+f"(d[2]), "+f"(d[3]), "+f"(d[4]), "+f"(d[5]), "+f"(d[6]), "+f"(d[7]),
        "+f"(d[8]), "+f"(d[9]), "+f"(d[10]), "+f"(d[11]), "+f"(d[12]), "+f"(d[13]), "+f"(d[14]), "+f"(d[15]),
        "+f"(d[16]), "+f"(d[17]), "+f"(d[18]), "+f"(d[19]), "+f"(d[20]), "+f"(d[21]), "+f"(d[22]), "+f"(d[23]),
        "+f"(d[24]), "+f"(d[25]), "+f"(d[26]), "+f"(d[27]), "+f"(d[28]), "+f"(d[29]), "+f"(d[30]), "+f"(d[31]),
        "+f"(d[32]), "+f"(d[33]), "+f"(d[34]), "+f"(d[35]), "+f"(d[36]), "+f"(d[37]), "+f"(d[38]), "+f"(d[39])
        : "l"(da), "l"(db));
}
__device__ __forceinline__ void wgmma_ss_n80_tatb(float (&d)[40], uint64_t da, uint64_t db) {
    asm volatile(
        "wgmma.mma_async.sync.aligned.m64n80k16.f32.bf16.bf16 {"
        "%0, %1, %2, %3, %4, %5, %6, %7, %8, %9, %10, %11, %12, %13, %14, %15, "
        "%16, %17, %18, %19, %20, %21, %22, %23, %24, %25, %26, %27, %28, %29, %30, %31, "
        "%32, %33, %34, %35, %36, %37, %38, %39"
        "}, %40, %41, 1, 1, 1, 1, 1;\n"
        :
        "+f"(d[0]), "+f"(d[1]), "+f"(d[2]), "+f"(d[3]), "+f"(d[4]), "+f"(d[5]), "+f"(d[6]), "+f"(d[7]),
        "+f"(d[8]), "+f"(d[9]), "+f"(d[10]), "+f"(d[11]), "+f"(d[12]), "+f"(d[13]), "+f"(d[14]), "+f"(d[15]),
        "+f"(d[16]), "+f"(d[17]), "+f"(d[18]), "+f"(d[19]), "+f"(d[20]), "+f"(d[21]), "+f"(d[22]), "+f"(d[23]),
        "+f"(d[24]), "+f"(d[25]), "+f"(d[26]), "+f"(d[27]), "+f"(d[28]), "+f"(d[29]), "+f"(d[30]), "+f"(d[31]),
        "+f"(d[32]), "+f"(d[33]), "+f"(d[34]), "+f"(d[35]), "+f"(d[36]), "+f"(d[37]), "+f"(d[38]), "+f"(d[39])
        : "l"(da), "l"(db));
}

__device__ __forceinline__ uint32_t exp2_fma(float t0, float t1) {
    uint32_t u = __byte_perm(__float_as_uint(t0), __float_as_uint(t1), 0x6521);
    uint32_t y, e, r;
    asm("lop3.b32 %0, %1, %2, %3, 0xEA;" : "=r"(y) : "r"(u), "r"(0x007F007F), "r"(0xBF00BF00));
    asm("lop3.b32 %0, %1, %2, %3, 0xEA;" : "=r"(e) : "r"(u), "r"(0x7F807F80), "r"(0x00030003));
    asm("fma.rn.bf16x2 %0, %1, %2, %3;" : "=r"(r) : "r"(u), "r"(y), "r"(e));
    return r;
}
__device__ __forceinline__ uint32_t exp2_mufu(float t0, float t1) { return pack_bf16(ex2(t0), ex2(t1)); }

template <int T0, int T1>
__device__ __forceinline__ void softmax_pv(float (&s)[64], uint32_t (&p)[32], float (&o)[12], uint64_t dv) {
#pragma unroll
    for (int t = T0; t < T1; t++) {
        if ((POLYMASK >> t) & 1) {
            p[2 * t] = exp2_fma(s[4 * t], s[4 * t + 1]);
            p[2 * t + 1] = exp2_fma(s[4 * t + 2], s[4 * t + 3]);
        } else {
            p[2 * t] = exp2_mufu(s[4 * t], s[4 * t + 1]);
            p[2 * t + 1] = exp2_mufu(s[4 * t + 2], s[4 * t + 3]);
        }
    }
#pragma unroll
    for (int t = 2 * T0; t < 2 * T1; t++) asm volatile("" : "+r"(p[t])::"memory");
    wg_fence();
#pragma unroll
    for (int kk = T0 / 2; kk < T1 / 2; kk++) wgmma_rs_n24_tb<1>(o, p[4 * kk], p[4 * kk + 1], p[4 * kk + 2], p[4 * kk + 3], dv + kk * 48);
}

__device__ __forceinline__ void load_q(uint32_t (&q)[6], int head, int row0, int lane) {
    const uint8_t* qg = g_qkv + (size_t)head * 196608 + (row0 >> 7) * 12288 + ((row0 & 127) >> 3) * 384 + lane * 4;
    q[0] = __ldcg((const uint32_t*)qg); q[1] = __ldcg((const uint32_t*)(qg + 384));
    q[2] = __ldcg((const uint32_t*)(qg + 128)); q[3] = __ldcg((const uint32_t*)(qg + 512));
    q[4] = __ldcg((const uint32_t*)(qg + 256)); q[5] = __ldcg((const uint32_t*)(qg + 640));
}
__device__ __forceinline__ void attn_store(float (&o)[12], int head, int rb, int warp, int lane) {
    const int g = lane >> 2;
    const float l0 = __shfl_sync(~0u, o[8], (lane & ~3) | 2), l1 = __shfl_sync(~0u, o[10], (lane & ~3) | 2);
    const float r0 = __fdividef(1.f, l0), r1 = __fdividef(1.f, l1);
    uint8_t* og = g_o + (size_t)(rb * 8 + (warp & 3) * 2) * 10240 + head * 320 + lane * 4;
#pragma unroll
    for (int t = 0; t < 3; t++) {
        uint32_t a = pack_bf16(o[4 * t] * r0, o[4 * t + 1] * r0), b = pack_bf16(o[4 * t + 2] * r1, o[4 * t + 3] * r1);
        asm volatile("movmatrix.sync.aligned.m8n8.trans.b16 %0, %0;" : "+r"(a));
        asm volatile("movmatrix.sync.aligned.m8n8.trans.b16 %0, %0;" : "+r"(b));
        if (t < 2 || g < 4) {
            *(uint32_t*)(og + t * 128) = a;
            *(uint32_t*)(og + t * 128 + 10240) = b;
        }
    }
    publish(warp >> 3);
}

__device__ __forceinline__ void attention_general(uint32_t sb, int head, int qb) {
    const int tid = threadIdx.x, warp = __shfl_sync(~0u, tid >> 5, 0), wg = warp >> 2, lane = tid & 31, c = lane & 3;
    const uint32_t bar = sb + SM_BAR;
    const uint64_t dK0 = mkdesc(sb, 128, 384, 0), dK1 = mkdesc(sb + 256, 0, 384, 0), dV = mkdesc(sb + 6144, 384, 128, 0);
#pragma unroll 1
    for (int blk = 0; blk < 2; blk++) {
        const int rb = blk * 16 + qb * 4 + wg;
        uint32_t q[6];
        load_q(q, head, rb * 64 + (warp & 3) * 16, lane);
        if (c >= 2) q[4] = q[5] = 0;
        pin(q);
        float o[12], s[64];
        uint32_t p[32];
#pragma unroll
        for (int i = 0; i < 12; i++) o[i] = 0.f;
        float m0 = -INFINITY, m1 = -INFINITY;
#pragma unroll 1
        for (int j = 0; j < 16; j++) {
            wg_fence();
            wgmma_rs_n128<0>(s, q[0], q[1], q[2], q[3], dK0 + j * 768);
            wgmma_rs_n128<1>(s, q[4], q[5], 0u, 0u, dK1 + j * 768);
            wg_commit();
            wg_wait<0>();
            pin(s);
            float n0 = m0, n1 = m1;
#pragma unroll
            for (int t = 0; t < 16; t++) {
                n0 = fmaxf(n0, fmaxf(s[4 * t], s[4 * t + 1]));
                n1 = fmaxf(n1, fmaxf(s[4 * t + 2], s[4 * t + 3]));
            }
#pragma unroll
            for (int m = 1; m < 4; m <<= 1) { n0 = fmaxf(n0, __shfl_xor_sync(~0u, n0, m)); n1 = fmaxf(n1, __shfl_xor_sync(~0u, n1, m)); }
            const float f0 = ex2(m0 - n0), f1 = ex2(m1 - n1);
            m0 = n0; m1 = n1;
#pragma unroll
            for (int t = 0; t < 3; t++) { o[4 * t] *= f0; o[4 * t + 1] *= f0; o[4 * t + 2] *= f1; o[4 * t + 3] *= f1; }
#pragma unroll
            for (int t = 0; t < 16; t++) {
                p[2 * t] = exp2_mufu(s[4 * t] - m0, s[4 * t + 1] - m0);
                p[2 * t + 1] = exp2_mufu(s[4 * t + 2] - m1, s[4 * t + 3] - m1);
            }
            pin(p);
            pin(o);
            wg_fence();
#pragma unroll
            for (int kk = 0; kk < 8; kk++) wgmma_rs_n24_tb<1>(o, p[4 * kk], p[4 * kk + 1], p[4 * kk + 2], p[4 * kk + 3], dV + j * 768 + kk * 48);
            wg_commit();
            wg_wait<0>();
            pin(o);
        }
        if (blk == 1 && lane == 0) { mbar_arrive(bar + 8 * B_HALF1); mbar_arrive(bar + 8 * B_FREE1); }
        attn_store(o, head, rb, warp, lane);
    }
}

__device__ __forceinline__ void helper_pre(float* red, int hi, const bf16* __restrict__ wo, const bf16* __restrict__ wgate,
                                        const bf16* __restrict__ wup, const bf16* __restrict__ wdown) {
    const int tid = threadIdx.x;
    const bf16* w = (hi >> 1) ? wup : wgate;
    const int co = tid % 96, rg = tid / 96;
    if (tid < 480) {
        const uint4* wp = (const uint4*)(w + (size_t)(rg * 128) * F_ + (hi & 1) * 768) + co;
        float a[8];
#pragma unroll
        for (int q = 0; q < 8; q++) a[q] = 0.f;
#pragma unroll 1
        for (int r = 0; r < 128; r += 16) {
            uint4 u[16];
#pragma unroll
            for (int i = 0; i < 16; i++) u[i] = __ldg(wp + (size_t)(r + i) * (F_ / 8));
#pragma unroll
            for (int i = 0; i < 16; i++) {
                a[0] += bf_lo(u[i].x); a[1] += bf_hi(u[i].x); a[2] += bf_lo(u[i].y); a[3] += bf_hi(u[i].y);
                a[4] += bf_lo(u[i].z); a[5] += bf_hi(u[i].z); a[6] += bf_lo(u[i].w); a[7] += bf_hi(u[i].w);
            }
        }
#pragma unroll
        for (int q = 0; q < 8; q++) red[rg * 768 + co * 8 + q] = a[q];
    }
    bar_sync(5, 512);
    if (tid >= 480 && tid < 496) {
        const int i = (tid - 480) + hi * 16;
        l2_prefetch((const uint8_t*)wo + i * 12800, 12800);
        l2_prefetch((const uint8_t*)wdown + i * 30720, 30720);
    }
#pragma unroll 1
    for (int i = tid; i < 768; i += 512)
        g_cs2[(hi >> 1) * F_ + (hi & 1) * 768 + i] = red[i] + red[768 + i] + red[1536 + i] + red[2304 + i] + red[3072 + i];
    bar_sync(5, 512);
    if (tid == 0) cnt_signal(C_CS2);
}

template <bool UP>
__device__ __forceinline__ void rgemm_load_ring(uint32_t sb, const Maps& maps, int pos, int kb, int i) {
    const uint32_t fb = sb + SM_BAR + 8 * (B_RF + 4 * UP + (i & 3)), dst = sb + SM_RING + (i & 3) * 16384;
    mbar_expect_tx(fb, 16384);
    if (UP) {
        tma2d(dst, &maps.wg, pos, kb * 64, fb);
        tma2d(dst + 8192, &maps.wu, pos, kb * 64, fb);
    } else {
        tma2d(dst, &maps.x, kb * 64, pos, fb);
    }
}
template <bool UP>
__device__ __forceinline__ void rgemm_load_res(uint32_t sb, const Maps& maps, int pos, int kb) {
    const uint32_t fb = sb + SM_BAR + 8 * (B_RA + kb);
    mbar_expect_tx(fb, 16384);
    if (UP) {
        tma2d(sb + kb * 16384, &maps.h, kb * 64, pos, fb);
    } else {
        tma2d(sb + kb * 16384, &maps.wqkv, pos, kb * 64, fb);
        tma2d(sb + kb * 16384 + 8192, &maps.wqkv, pos + 64, kb * 64, fb);
    }
}
template <bool UP>
__device__ __forceinline__ void rgemm_produce(uint32_t sb, const Maps& maps, int rpos, int spos) {
    int kb = 4;
#pragma unroll 1
    for (int i = 4; i < (UP ? 30 : 20); i++) {
        mbar_wait(sb + SM_BAR + 8 * (B_RE + 4 * UP + (i & 3)), ((i >> 2) - 1) & 1);
        if (!UP) TRACE(0, i);
        rgemm_load_ring<UP>(sb, maps, spos, kb, i);
        if (i < 9) rgemm_load_res<UP>(sb, maps, rpos, i + 1);
        if (!UP) TRACE(1, i);
        if (++kb == 10) { kb = 0; spos += UP ? 64 : 1024; }
    }
}
template <bool UP>
__device__ __forceinline__ void rgemm_phase(float (&acc)[64], uint32_t sb, uint32_t rpar, int p, int warp, int lane) {
    const uint32_t bar = sb + SM_BAR;
#pragma unroll
    for (int i = 0; i < 64; i++) acc[i] = 0.f;
    if (!UP && threadIdx.x == 0) TRACE(1, 3);
    if (p > 0) mbar_wait(bar + 8 * (B_TURN + UP + p - 1), 0);
    const uint64_t da0 = mkdesc(sb + (UP ? 0 : SM_RING) + ((warp >> 2) & 1) * 8192, 16, 1024, 1);
    const uint64_t db0 = mkdesc(sb + (UP ? SM_RING : 0), 8192, 1024, 1);
#pragma unroll 1
    for (int kb = 0, i = p * 10; kb < 10; kb++, i++) {
        if (p == 0) mbar_wait(bar + 8 * (B_RA + kb), rpar);
        mbar_wait(bar + 8 * (B_RF + 4 * UP + (i & 3)), (i >> 2) & 1);
        if (kb == 0) STAMP(UP ? 9 : 1);
        const uint64_t da = da0 + (UP ? kb : i & 3) * 1024, db = db0 + (UP ? i & 3 : kb) * 1024;
        wg_fence();
#pragma unroll
        for (int kk = 0; kk < 4; kk++) {
            wgmma_ss_n128_tb(acc, da + kk * 2, db + kk * 128);
            if (kk == 0) {
                wg_commit();
                wg_wait<1>();
                if (kb > 0 && lane == 0) mbar_arrive(bar + 8 * (B_RE + 4 * UP + ((i - 1) & 3)));
                wg_fence();
            }
        }
        wg_commit();
    }
    if ((warp & 7) == 0 && lane == 0 && p < 1 + UP) mbar_arrive(bar + 8 * (B_TURN + UP + p));
    wg_wait<0>();
    pin(acc);
    if (lane == 0) mbar_arrive(bar + 8 * (B_RE + 4 * UP + ((p * 10 + 9) & 3)));
}

__global__ void __cluster_dims__(2, 1, 1) __launch_bounds__(NTHR, 1)
block_kernel(const __grid_constant__ Maps maps, const bf16* __restrict__ x, const bf16* __restrict__ wqkv,
             const bf16* __restrict__ wo, const bf16* __restrict__ wgate, const bf16* __restrict__ wup,
             const bf16* __restrict__ wdown, bf16* __restrict__ out, int phases) {
    extern __shared__ __align__(1024) uint8_t smem[];
    const uint32_t sb = (uint32_t)__cvta_generic_to_shared(smem);
    const uint32_t bar = sb + SM_BAR;
    const int tid = threadIdx.x, warp = __shfl_sync(~0u, tid >> 5, 0), wg = warp >> 2, lane = tid & 31, g = lane >> 2, c = lane & 3;
    const int cl = blockIdx.x >> 1;
    const int b = 2 * ((cl & 7) * 8 + min(cl & 7, 2) + (cl >> 3)) + (blockIdx.x & 1);
    const bool main_cta = b < 128;
    const int qm = ((b >> 4) & 1) * 4 + (b & 3), qn = (b >> 5) * 4 + ((b >> 2) & 3);
    const int qcol = qn * 120 - (qn & 1) * 8;
    const int head = b >> 2, qb = b & 3;
    const int ct = b % 5, tt = b / 5;
    const int mt = b >> 3, nt = b & 7;

    STAMP(0); STAMPG(0);
    if (warp == 16) {
        if (elect_one()) {
#pragma unroll
            for (int i = 0; i < B_RA + 10; i++) mbar_init(bar + 8 * i, 1);
#pragma unroll
            for (int i = B_RE; i < B_RE + 4; i++) mbar_init(bar + 8 * i, 8);
            asm volatile("fence.proxy.async.shared::cta;" ::: "memory");
        }
        __syncwarp();
        asm volatile("bar.arrive 0, 640;" ::: "memory");
        if (main_cta && (phases & PH_QKV) && elect_one()) {
#pragma unroll 1
            for (int i = 0; i < 5; i++) {
                rgemm_load_res<false>(sb, maps, qcol, i);
                if (i < 4) rgemm_load_ring<false>(sb, maps, qm * 128, i, i);
            }
            TRACE(1, 0);
            rgemm_produce<false>(sb, maps, qcol, qm * 128);
        }
        __syncwarp();
    } else {
        if (warp == 17 && elect_one()) {
            prefetch_map(&maps.x);
#pragma unroll
            for (int i = B_RA + 10; i < B_NUM; i++)
                if (i < B_RE || i >= B_RE + 4) mbar_init(bar + 8 * i, i < B_TE ? 1 : i < B_STAT ? 8 : i == B_STAT ? 10 : i == B_STAT2 ? 3 : 16);
            asm volatile("fence.proxy.async.shared::cta;" ::: "memory");
        }
        __syncwarp();
        bar_sync(0, 640);
    }
    if (tid == 0) TRACE(1, 1);

    if (__builtin_expect(wg == 4, 1)) {
        asm volatile("setmaxnreg.dec.sync.aligned.u32 32;");
        const uint32_t epoch = __ldcg(g_cnt + C_EPOCH * 32);
        if (warp == 16) {
            if (main_cta && (phases & PH_ATT)) {
                const uint8_t* kv = g_qkv + (size_t)(32 + head) * 196608;
#pragma unroll 1
                for (int hf = 0; hf < 2; hf++) {
                    cnt_wait(lane < 3, C_QKV + hf * 16 + (lane * 32 + head) / 6, (epoch + 1) * 8);
                    if (elect_one()) {
                        if (hf == 0) mbar_arrive(bar + 8 * B_DEP1);
                        fence_async_global();
                        if (hf == 1 && (phases & PH_QKV)) mbar_wait(bar + 8 * B_FREE0, 0);
#pragma unroll 1
                        for (int ch = hf * 4; ch < hf * 4 + 4; ch++) {
                            if (ch == 1) mbar_wait(bar + 8 * B_AF, 0);
                            mbar_expect_tx(bar + 8 * (B_AF + ch), 24576);
                            bulk_g2s(sb + ch * 24576, kv + ch * 24576, 24576, bar + 8 * (B_AF + ch));
                        }
                    }
                    __syncwarp();
                }
                const uint4 a = __ldcg((const uint4*)(g_nrm + head * 128) + lane);
                const uint4 k4 = __ldcg((const uint4*)(g_nrm + (32 + head) * 128) + lane);
                const uint4 v4 = __ldcg((const uint4*)(g_nrm + (64 + head) * 128) + lane);
                const float nq = __uint_as_float(__reduce_max_sync(~0u, max(max(a.x, a.y), max(a.z, a.w))));
                const float nk = __uint_as_float(__reduce_max_sync(~0u, max(max(k4.x, k4.y), max(k4.z, k4.w))));
                const float nv = __uint_as_float(__reduce_max_sync(~0u, max(max(v4.x, v4.y), max(v4.z, v4.w))));
                if (lane == 0) {
                    *(volatile uint32_t*)(smem + SM_VER) = (nq * nk <= 3300.f) && (nq <= 1e18f) && (nk <= 1e18f) && (nv <= 1e24f) && (nv >= 1e-24f);
                    mbar_arrive(bar + 8 * B_VER);
                }
                __syncwarp();
            }
            const int rb0 = (tt * 80) >> 7, rb1 = min((tt * 80 + 79) >> 7, 15);
            int it0 = 0;
            if (b < 130 && (phases & PH_OPJ)) {
                if (elect_one()) {
#pragma unroll 1
                    for (int i = 0; i < 8; i++) {
                        if ((i == 0 || i == 5) && (phases & (main_cta ? PH_ATT : PH_PRE))) mbar_wait(bar + 8 * (i ? B_FREE1 : B_HALF1), 0);
                        mbar_expect_tx(bar + 8 * (B_TF + i), 26624);
                        tma2d(sb + i * 26624, &maps.wo, ct * 128, i * 64, bar + 8 * (B_TF + i));
                        tma2d(sb + i * 26624 + 8192, &maps.wo, ct * 128 + 64, i * 64, bar + 8 * (B_TF + i));
                    }
                }
                __syncwarp();
                cnt_wait(rb0 + lane <= rb1, C_ATT + rb0 + lane, (epoch + 1) * 32);
                if (elect_one()) {
                    fence_async_global();
#pragma unroll 1
                    for (int i = 0; i < 10; i++) {
                        const uint32_t s = i & 7, fb = bar + 8 * (B_TF + s);
                        if (i >= 8) {
                            mbar_wait(bar + 8 * (B_TE + s), 0);
                            mbar_expect_tx(fb, 26624);
                            tma2d(sb + s * 26624, &maps.wo, ct * 128, i * 64, fb);
                            tma2d(sb + s * 26624 + 8192, &maps.wo, ct * 128 + 64, i * 64, fb);
                        }
                        tma2d(sb + s * 26624 + 16384, &maps.o, i * 128, tt * 10, fb);
                    }
                }
                __syncwarp();
                it0 = 10;
            }
            if (main_cta && (phases & PH_UP)) {
                if (elect_one()) {
                    if (phases & PH_OPJ) mbar_wait(bar + 8 * (B_TE + 7), 0);
#pragma unroll 1
                    for (int i = 0; i < 4; i++) rgemm_load_ring<true>(sb, maps, nt * 192, i, i);
                }
                __syncwarp();
                const int t0 = (mt * 128) / 80, t1 = (mt * 128 + 127) / 80;
                cnt_wait(t0 + lane <= t1, C_H + t0 + lane, (epoch + 1) * 5);
                if (elect_one()) {
                    mbar_arrive(bar + 8 * B_DEP3);
                    fence_async_global();
                    if (phases & PH_OPJ) mbar_wait(bar + 8 * B_STG, 0);
#pragma unroll 1
                    for (int i = 0; i < 5; i++) rgemm_load_res<true>(sb, maps, mt * 128, i);
                    rgemm_produce<true>(sb, maps, mt * 128, nt * 192);
                }
                __syncwarp();
            }
            if (b < 130 && (phases & PH_DN)) {
                cnt_wait(rb0 + lane <= rb1, C_ACT + rb0 + lane, (epoch + 1) * 16);
                if (elect_one()) {
                    fence_async_global();
                    if (main_cta && (phases & PH_UP)) mbar_wait(bar + 8 * B_FREE3, 0);
                    if (phases & PH_OPJ) mbar_wait(bar + 8 * B_STG, 0);
#pragma unroll 1
                    for (int j = 0; j < 24; j++) {
                        const int i = it0 + j, kb = j >= 16 ? (j - 16) * 3 + 2 : (j >> 1) * 3 + (j & 1);
                        const uint32_t s = i & 7, fb = bar + 8 * (B_TF + s);
                        if (j >= INFL) mbar_wait(bar + 8 * (B_TF + ((i - INFL) & 7)), ((i - INFL) >> 3) & 1);
                        if (j >= 8) mbar_wait(bar + 8 * (B_TE + s), ((i >> 3) - 1) & 1);
                        TRACE(0, 32 + j);
                        mbar_expect_tx(fb, 26624);
                        tma2d(sb + s * 26624, &maps.wd, ct * 128, kb * 64, fb);
                        tma2d(sb + s * 26624 + 8192, &maps.wd, ct * 128 + 64, kb * 64, fb);
                        if (j == 16) { mbar_wait(bar + 8 * B_DEP4, 0); fence_async_global(); }
                        tma2d(sb + s * 26624 + 16384, &maps.act, kb * 128, tt * 10, fb);
                        TRACE(1, 32 + j);
                    }
                }
                __syncwarp();
            }
            if ((phases & PH_DN) && lane == 0) {
                const uint32_t ticket = atomicAdd(g_cnt + C_DONE * 32, 1u);
                if (ticket + 1 == (epoch + 1) * NCTA) g_cnt[C_EPOCH * 32] = epoch + 1;
            }
        } else if (b < 130) {
            const int t = tid - 544;
            if (t == 0) {
                prefetch_map(&maps.wo); prefetch_map(&maps.o); prefetch_map(&maps.h); prefetch_map(&maps.wg);
                prefetch_map(&maps.wu); prefetch_map(&maps.act); prefetch_map(&maps.wd);
            }
            auto signal = [&](int cn) { bar_sync(warp - 17, 288); if (lane == 0) cnt_signal(cn); __syncwarp(); };
            if (main_cta && warp >= 18 && (phases & PH_QKV)) {
                const ulonglong2* sp = (const ulonglong2*)(g_stat1 + (warp - 18) * 1024 + qm * 128) + lane;
#pragma unroll
                for (int h = 0; h < 2; h++) {
                    ulonglong2 v;
#pragma unroll 1
                    for (int it = 0; it < 1000000; it++) {
                        asm volatile("ld.volatile.global.v2.u64 {%0, %1}, [%2];" : "=l"(v.x), "=l"(v.y) : "l"(sp + h * 32) : "memory");
                        if ((((v.x >> 32) ^ epoch) & ((v.y >> 32) ^ epoch) & 1) != 0) break;
                        __nanosleep(100);
                    }
                    ((ulonglong2*)(smem + SM_CS + 512))[(warp - 18) * 64 + h * 32 + lane] = v;
                }
                __syncwarp();
                if (lane == 0) mbar_arrive(bar + 8 * B_STAT);
                if (lane == 0) TRACE(3, warp - 18);
            }
            if (warp >= 18) {
                if (main_cta && (phases & PH_QKV)) signal(C_QKV + (warp - 18) * 16 + qn);
                if (main_cta && (phases & PH_ATT)) { signal(C_ATT + qb * 2 + warp - 18); signal(C_ATT + 8 + qb * 2 + warp - 18); }
                if (warp == 19 && (phases & PH_OPJ)) signal(C_H + tt);
            }
            if (main_cta && (phases & PH_UP)) {
                mbar_wait(bar + 8 * B_DEP3, 0);
                if (warp == 17) {
                    cnt_wait(lane == 0, C_CS2, (epoch + 1) * 4);
#pragma unroll
                    for (int i = lane; i < 96; i += 32)
                        ((float4*)(smem + SM_CS))[i] = __ldcg((const float4*)(g_cs2 + (i >= 48 ? F_ - 192 : 0) + nt * 192) + i);
                } else {
                    float4 a = make_float4(0.f, 0.f, 0.f, 0.f);
#pragma unroll
                    for (int i = 0; i < 5; i++) {
                        const float4 u = __ldcg((const float4*)(g_part2 + i * S_ + mt * 128) + t - 32);
                        a.x += u.x; a.y += u.y; a.z += u.z; a.w += u.w;
                    }
                    const float m0 = a.x * (1.f / D_), m1 = a.z * (1.f / D_);
                    ((float4*)(smem + SM_CS + 1536))[t - 32] = make_float4(m0, rsqrtf(fmaxf(a.y * (1.f / D_) - m0 * m0, 0.f) + 1e-5f),
                                                                           m1, rsqrtf(fmaxf(a.w * (1.f / D_) - m1 * m1, 0.f) + 1e-5f));
                }
                __syncwarp();
                if (lane == 0) mbar_arrive(bar + 8 * B_STAT2);
                if (warp >= 18) signal(C_ACT + mt);
                if (warp == 18) signal(C_ACT + 16 + mt);
            }
            if (warp == 17 && (phases & PH_DN)) {
                const int rb0 = (tt * 80) >> 7, rb1 = min((tt * 80 + 79) >> 7, 15);
                if (main_cta && (phases & PH_UP)) mbar_wait(bar + 8 * B_FREE3, 0);
                cnt_wait(rb0 + lane <= rb1, C_ACT + 16 + rb0 + lane, (epoch + 1) * 8);
                if (lane == 0) mbar_arrive(bar + 8 * B_DEP4);
                if (lane == 0) TRACE(2, 48);
            }
        }
    } else {
        const int pair = wg >> 1;
        if (tid == 0) TRACE(1, 2);
        float* s_cs = (float*)(smem + SM_CS);
        if (main_cta && (phases & PH_PRE) && pair == 1) {
            const uint32_t epoch = __ldcg(g_cnt + C_EPOCH * 32);
            const uint2* xr = (const uint2*)(x + (size_t)(b * 16 + (warp & 7) * 2) * D_) + lane;
            uint2 xv[2][5];
#pragma unroll
            for (int i = 0; i < 5; i++) { xv[0][i] = __ldg(xr + i * 32); xv[1][i] = __ldg(xr + i * 32 + 160); }
#pragma unroll
            for (int r = 0; r < 2; r++) {
                float sm = 0.f;
#pragma unroll
                for (int i = 0; i < 5; i++) sm += (bf_lo(xv[r][i].x) + bf_hi(xv[r][i].x)) + (bf_lo(xv[r][i].y) + bf_hi(xv[r][i].y));
#pragma unroll
                for (int m = 16; m; m >>= 1) sm += __shfl_xor_sync(~0u, sm, m);
                const float mean = sm * (1.f / D_);
                float sq = 0.f;
#pragma unroll
                for (int i = 0; i < 5; i++) {
                    const float d0 = bf_lo(xv[r][i].x) - mean, d1 = bf_hi(xv[r][i].x) - mean, d2 = bf_lo(xv[r][i].y) - mean, d3 = bf_hi(xv[r][i].y) - mean;
                    sq += fmaf(d0, d0, d1 * d1) + fmaf(d2, d2, d3 * d3);
                }
#pragma unroll
                for (int m = 16; m; m >>= 1) sq += __shfl_xor_sync(~0u, sq, m);
                const uint32_t rs = (__float_as_uint(rsqrtf(sq * (1.f / D_) + 1e-5f)) & ~1u) | (~epoch & 1u);
                if (lane == 0)
                    asm volatile("st.volatile.global.u64 [%0], %1;" ::"l"(g_stat1 + b * 16 + (warp & 7) * 2 + r),
                                 "l"((uint64_t)__float_as_uint(mean) | ((uint64_t)rs << 32)) : "memory");
            }
        }

        if (tid == 256) TRACE(3, 2);
        if (main_cta && (phases & PH_QKV)) {
            if (pair == 1) {
                float cs[4] = {0.f, 0.f, 0.f, 0.f}, cs2[4] = {0.f, 0.f, 0.f, 0.f};
                const uint32_t wa = sb + (wg & 1) * 8192 + ((lane & 7) + (lane >> 4) * 8) * 128 + (((2 * (warp & 3) + ((lane >> 3) & 1)) ^ (lane & 7)) << 4);
#pragma unroll 1
                for (int kb = 0; kb < 10; kb++) {
                    mbar_wait(bar + 8 * (B_RA + kb), 0);
#pragma unroll
                    for (int kk = 0; kk < 4; kk++) {
                        uint32_t a[4];
                        asm volatile("ldmatrix.sync.aligned.m8n8.x4.trans.shared.b16 {%0, %1, %2, %3}, [%4];"
                                     : "=r"(a[0]), "=r"(a[1]), "=r"(a[2]), "=r"(a[3]) : "r"(wa + kb * 16384 + kk * 2048) : "memory");
                        if (kk & 1) mma16816(cs2, a, 0x3F803F80u, 0x3F803F80u); else mma16816(cs, a, 0x3F803F80u, 0x3F803F80u);
                    }
                }
                if (c == 0) { s_cs[(warp & 7) * 16 + g] = cs[0] + cs2[0]; s_cs[(warp & 7) * 16 + g + 8] = cs[2] + cs2[2]; }
                __syncwarp();
                if (lane == 0) mbar_arrive(bar + 8 * B_STAT);
                STAMP(12);
            }
            float acc[64];
            rgemm_phase<false>(acc, sb, 0, pair, warp, lane);
            if (pair == 1 && lane == 0) mbar_arrive(bar + 8 * B_FREE0);
            if (pair == 0) STAMP(12);
            mbar_wait(bar + 8 * B_STAT, 0);
            STAMP(2);
            if (qn & 1) {
#pragma unroll
                for (int i = 0; i < 60; i++) acc[i] = acc[i + 4];
            }
            const int rl = (warp & 7) * 16;
            const float2* s_st = (const float2*)(smem + SM_CS + 512) + pair * 128;
            const float2 st0 = s_st[rl + g], st1 = s_st[rl + g + 8];
            uint8_t* base = g_qkv + (pair * 8 + qm) * 12288 + (rl >> 3) * 384 + g * 16;
            const int off_al = 4 * c;
            const int off_sh = c < 2 ? 8 + 4 * c : 128 + 4 * (c - 2);
            const int off_bd = c < 2 ? 256 + 4 * c : 196608 + 4 * (c - 2);
            constexpr float QSCALE = 0.22360679774997896f * 1.4426950408889634f;
#pragma unroll
            for (int hp = 0; hp < 3; hp++) {
                const int slot = qn * 6 + hp * 2;
                const float sc = slot < 32 ? QSCALE : 1.f;
                const float r0 = st0.y * sc, r1 = st1.y * sc;
                float nA0 = 0.f, nA1 = 0.f, nB0 = 0.f, nB1 = 0.f;
                uint8_t* hb = base + (size_t)(slot * 196608 - (slot >= 64 ? 32 * 196608 - 6144 : 0));
#pragma unroll
                for (int jj = 0; jj < 5; jj++) {
                    const int j = hp * 5 + jj;
                    const float2 cs = *(const float2*)(s_cs + (qn & 1) * 8 + 8 * j + 2 * c);
                    const float v0 = r0 * fmaf(-st0.x, cs.x, acc[4 * j]), v1 = r0 * fmaf(-st0.x, cs.y, acc[4 * j + 1]);
                    const float v2 = r1 * fmaf(-st1.x, cs.x, acc[4 * j + 2]), v3 = r1 * fmaf(-st1.x, cs.y, acc[4 * j + 3]);
                    int off;
                    if (jj < 2) {
                        off = jj * 128 + off_al;
                        nA0 = fmaf(v0, v0, fmaf(v1, v1, nA0)); nA1 = fmaf(v2, v2, fmaf(v3, v3, nA1));
                    } else if (jj == 2) {
                        off = off_bd;
                        const float q0 = fmaf(v0, v0, v1 * v1), q1 = fmaf(v2, v2, v3 * v3);
                        if (c < 2) { nA0 += q0; nA1 += q1; } else { nB0 = q0; nB1 = q1; }
                    } else {
                        off = 196608 + (jj - 3) * 128 + off_sh;
                        nB0 = fmaf(v0, v0, fmaf(v1, v1, nB0)); nB1 = fmaf(v2, v2, fmaf(v3, v3, nB1));
                    }
                    *(uint32_t*)(hb + off) = pack_bf16(v0, v1);
                    *(uint32_t*)(hb + off + 384) = pack_bf16(v2, v3);
                }
                if (slot >= 32) {
                    const int grp = (rl >> 3) + (c & 1);
                    const uint32_t lo = slot >= 64 ? 0x00003F80u : (((POLYMASK >> grp) & 1) ? 0x3F803F80u : 0u);
                    *(uint2*)(hb + (c >> 1) * 196608 + (c & 1) * 384 + 256 + 8) = make_uint2(lo, 0u);
                }
                uint32_t pa = pack_bf16(nA0, nA1), pb = pack_bf16(nB0, nB1);
#pragma unroll
                for (int m = 1; m < 4; m <<= 1) {
                    const uint32_t ta = __shfl_xor_sync(~0u, pa, m), tb = __shfl_xor_sync(~0u, pb, m);
                    asm("add.rn.bf16x2 %0, %0, %1;" : "+r"(pa) : "r"(ta));
                    asm("add.rn.bf16x2 %0, %0, %1;" : "+r"(pb) : "r"(tb));
                }
                const uint32_t mA = __reduce_max_sync(~0u, max((pa << 16) & 0x7FFF0000u, pa & 0x7FFF0000u));
                const uint32_t mB = __reduce_max_sync(~0u, max((pb << 16) & 0x7FFF0000u, pb & 0x7FFF0000u));
                if (lane < 2) g_nrm[(slot + lane) * 128 + (pair * 8 + qm) * 8 + (warp & 7)] = __uint_as_float(lane ? mB : mA);
            }
            publish(pair);
            STAMP(3);
        }

        asm volatile("setmaxnreg.inc.sync.aligned.u32 112;");
        if (main_cta && (phases & PH_ATT)) {
            mbar_wait(bar + 8 * B_DEP1, 0);
            STAMP(4);
            const uint64_t dK0 = mkdesc(sb, 128, 384, 0), dK1 = mkdesc(sb + 256, 0, 384, 0), dV = mkdesc(sb + 6144, 384, 128, 0);
            uint32_t qa[6];
            load_q(qa, head, (qb * 4 + wg) * 64 + (warp & 3) * 16, lane);
            bool fast = true;
#pragma unroll 1
            for (int blk = 0; blk < 2; blk++) {
                uint32_t q[8];
#pragma unroll
                for (int i = 0; i < 6; i++) q[i] = qa[i];
                q[6] = q[7] = 0;
                if (c == 3) q[4] = q[5] = 0;
                if (c == 2) { q[4] = q[5] = 0xBFCC43C0u; q[6] = 0x0000BBAAu; q[7] = 0x8000BBAAu; }
                pin(q);
                float o[12], s[64];
                uint32_t p[32];
#pragma unroll
                for (int i = 0; i < 12; i++) o[i] = 0.f;
                pin(o);
                uint64_t bk0 = dK0, bk1 = dK1, bv = dV;
#pragma unroll 1
                for (int jj = 0; jj < 8; jj++, bk0 += 1536, bk1 += 1536, bv += 1536) {
                    if (blk == 0) mbar_wait(bar + 8 * (B_AF + jj), 0);
                    else if (jj == 5 && lane == 0) mbar_arrive(bar + 8 * B_HALF1);
#pragma unroll
                    for (int u = 0; u < 2; u++) {
                        wg_fence();
                        wgmma_rs_n128<0>(s, q[0], q[1], q[2], q[3], bk0 + u * 768);
                        wgmma_rs_n128<1>(s, q[4], q[5], q[6], q[7], bk1 + u * 768);
                        wg_commit();
                        wg_wait<0>();
                        pin(s);
                        softmax_pv<0, 8>(s, p, o, bv + u * 768);
                        softmax_pv<8, 16>(s, p, o, bv + u * 768);
                        wg_commit();
                        wg_wait<0>();
                        pin(o);
                    }
                }
                if (blk == 0) {
                    load_q(qa, head, (16 + qb * 4 + wg) * 64 + (warp & 3) * 16, lane);
                    mbar_wait(bar + 8 * B_VER, 0);
                    fast = __all_sync(~0u, *(volatile uint32_t*)(smem + SM_VER) != 0);
                    if (!fast) break;
                } else if (lane == 0) {
                    mbar_arrive(bar + 8 * B_FREE1);
                }
                attn_store(o, head, blk * 16 + qb * 4 + wg, warp, lane);
            }
            if (__builtin_expect(!fast, 0)) attention_general(sb, head, qb);
        }
        if (__builtin_expect(!main_cta, 0) && (phases & PH_PRE)) {
            helper_pre((float*)smem, b - 128, wo, wgate, wup, wdown);
            if (lane == 0) { mbar_arrive(bar + 8 * B_HALF1); mbar_arrive(bar + 8 * B_FREE1); }
        }
        STAMP(5);

        int it0 = 0;
#pragma unroll 1
        for (int down = 0; down < 2; down++) {
            if (b < 130 && (phases & (down ? PH_DN : PH_OPJ))) {
                const int it1 = it0 + (down ? 24 : 10);
                const uint32_t stg = ((it1 + 2) & 7) * 26624;
                if (pair == down) {
                    float acc[40];
#pragma unroll
                    for (int i = 0; i < 40; i++) acc[i] = 0.f;
                    const uint64_t da0 = mkdesc(sb + (wg & 1) * 8192, 0, 1024, 1), db0 = mkdesc(sb + 16384, 128, 1024, 0);
#pragma unroll 1
                    for (int i = it0; i < it1; i++) {
                        const int s = i & 7;
                        mbar_wait(bar + 8 * (B_TF + s), (i >> 3) & 1);
                        if (down) {
                            wg_fence();
#pragma unroll
                            for (int kk = 0; kk < 4; kk++) wgmma_ss_n80_ta(acc, da0 + s * 1664 + kk * 128, db0 + s * 1664 + kk * 16);
                            wg_commit();
                        } else {
                            wg_fence();
#pragma unroll
                            for (int kk = 0; kk < 4; kk++) wgmma_ss_n80_tatb(acc, da0 + s * 1664 + kk * 128, db0 + s * 1664 + kk * 16);
                            wg_commit();
                        }
                        wg_wait<1>();
                        if (i > it0 && lane == 0) mbar_arrive(bar + 8 * (B_TE + ((i - 1) & 7)));
                    }
                    wg_wait<0>();
                    pin(acc);
                    if (lane == 0) mbar_arrive(bar + 8 * (B_TE + ((it1 - 1) & 7)));
                    mbar_wait(bar + 8 * (B_TE + ((it1 + 2) & 7)), ((it1 - 6) >> 3) & 1);
                    STAMP(down ? 13 : 7);
                    const uint32_t a0 = sb + stg + (((lane >> 4) << 3) + (lane & 7)) * 256 + (((2 * (warp & 7) + ((lane >> 3) & 1)) ^ (lane & 7)) << 4);
#pragma unroll
                    for (int j = 0; j < 10; j += 2) {
                        uint32_t r0 = pack_bf16(acc[4 * j], acc[4 * j + 1]), r1 = pack_bf16(acc[4 * j + 2], acc[4 * j + 3]);
                        uint32_t r2 = pack_bf16(acc[4 * j + 4], acc[4 * j + 5]), r3 = pack_bf16(acc[4 * j + 6], acc[4 * j + 7]);
                        asm volatile("stmatrix.sync.aligned.m8n8.x4.trans.shared.b16 [%0], {%1, %2, %3, %4};" ::"r"(a0 + j * 2048), "r"(r0), "r"(r1), "r"(r2), "r"(r3) : "memory");
                    }
                    asm volatile("bar.arrive 5, 512;" ::: "memory");
                } else {
                    const int t = tid & 255;
                    const size_t goff = (size_t)(tt * 80 + (t >> 4)) * D_ + ct * 128 + (t & 15) * 8;
                    const bf16* resid = (down ? g_h : x) + goff;
                    bf16* dst = (down ? out : g_h) + goff;
                    const int nv = tt == 25 ? 3 : 5;
                    if (down && (phases & PH_OPJ)) mbar_wait(bar + 8 * B_STG, 0);
                    uint4 rv[5];
#pragma unroll
                    for (int i = 0; i < 5; i++) {
                        rv[i] = make_uint4(0, 0, 0, 0);
                        if (i < nv) rv[i] = __ldcg((const uint4*)(resid + i * 16 * D_));
                    }
                    bar_sync(5, 512);
                    const uint8_t* sp = smem + stg + (t >> 4) * 256 + (((t & 15) ^ ((t >> 4) & 7)) << 4);
#pragma unroll
                    for (int i = 0; i < 5; i++) {
                        if (i < nv) {
                            const uint4 v = *(const uint4*)(sp + i * 4096);
                            uint4 r;
                            r.x = pack_bf16(bf_lo(v.x) + bf_lo(rv[i].x), bf_hi(v.x) + bf_hi(rv[i].x));
                            r.y = pack_bf16(bf_lo(v.y) + bf_lo(rv[i].y), bf_hi(v.y) + bf_hi(rv[i].y));
                            r.z = pack_bf16(bf_lo(v.z) + bf_lo(rv[i].z), bf_hi(v.z) + bf_hi(rv[i].z));
                            r.w = pack_bf16(bf_lo(v.w) + bf_lo(rv[i].w), bf_hi(v.w) + bf_hi(rv[i].w));
                            *(uint4*)(dst + i * 16 * D_) = r;
                            if (!down) {
                                const float f[8] = {bf_lo(r.x), bf_hi(r.x), bf_lo(r.y), bf_hi(r.y), bf_lo(r.z), bf_hi(r.z), bf_lo(r.w), bf_hi(r.w)};
                                float sm = 0.f, sq = 0.f;
#pragma unroll
                                for (int q = 0; q < 8; q++) { sm += f[q]; sq = fmaf(f[q], f[q], sq); }
#pragma unroll
                                for (int m = 1; m < 16; m <<= 1) { sm += __shfl_xor_sync(~0u, sm, m); sq += __shfl_xor_sync(~0u, sq, m); }
                                if ((lane & 15) == 0) g_part2[ct * S_ + tt * 80 + (t >> 4) + 16 * i] = make_float2(sm, sq);
                            }
                        }
                    }
                    if (!down) {
                        __syncwarp();
                        if (lane == 0) mbar_arrive(bar + 8 * B_STG);
                        publish(1);
                    }
                }
                it0 = it1;
            }
            if (down) break;
            STAMP(8);

            if (main_cta && (phases & PH_UP)) {
                const uint32_t rpar = (phases & PH_QKV) ? 1 : 0;
#pragma unroll 1
                for (int p = pair; p < 3; p += 2) {
                    float acc[64];
                    rgemm_phase<true>(acc, sb, rpar, p, warp, lane);
                    if (p == 2 && lane == 0) mbar_arrive(bar + 8 * B_FREE3);
                    mbar_wait(bar + 8 * B_STAT2, 0);
                    STAMP(p == 0 ? 6 : 10);
                    const int rl = (warp & 7) * 16;
                    const float2* s_st = (const float2*)(smem + SM_CS + 1536);
                    const float2 st0 = s_st[rl + g], st1 = s_st[rl + g + 8];
                    uint8_t* ag = g_act + (size_t)(mt * 16 + (rl >> 3)) * 24576 + (nt * 24 + p * 8) * 128 + lane * 4;
                    const float hr0 = 0.5f * st0.y, hr1 = 0.5f * st1.y;
#pragma unroll
                    for (int j = 0; j < 8; j++) {
                        const float2 cg = *(const float2*)(s_cs + p * 64 + 8 * j + 2 * c), cu = *(const float2*)(s_cs + 192 + p * 64 + 8 * j + 2 * c);
                        float r[4];
#pragma unroll
                        for (int e = 0; e < 4; e++) {
                            const float mean = e < 2 ? st0.x : st1.x;
                            const float gt = (e < 2 ? st0.y : st1.y) * fmaf(-mean, (e & 1) ? cg.y : cg.x, acc[4 * j + e]);
                            const float uh = (e < 2 ? hr0 : hr1) * fmaf(-mean, (e & 1) ? cu.y : cu.x, acc[32 + 4 * j + e]);
                            const float z = gt * fmaf(gt * gt, 0.7978845608028654f * 0.044715f, 0.7978845608028654f);
                            float th;
                            asm("tanh.approx.f32 %0, %1;" : "=f"(th) : "f"(z));
                            const float hg = gt * uh;
                            r[e] = fmaf(hg, th, hg);
                        }
                        *(uint32_t*)(ag + j * 128) = pack_bf16(r[0], r[1]);
                        *(uint32_t*)(ag + j * 128 + 24576) = pack_bf16(r[2], r[3]);
                    }
                    publish(pair);
                }
            }
            STAMP(11);
        }
        STAMP(14); STAMPG(1);
    }
}

typedef CUresult (*EncodeFn)(CUtensorMap*, CUtensorMapDataType, cuuint32_t, void*, const cuuint64_t*, const cuuint64_t*,
                             const cuuint32_t*, const cuuint32_t*, CUtensorMapInterleave, CUtensorMapSwizzle,
                             CUtensorMapL2promotion, CUtensorMapFloatOOBfill);

static void enc2d(EncodeFn enc, CUtensorMap* m, CUtensorMapDataType dt, const void* p, uint64_t d0, uint64_t d1, uint64_t stride,
                  uint32_t b0, uint32_t b1, CUtensorMapSwizzle sw) {
    cuuint64_t dim[2] = {d0, d1}, str[1] = {stride};
    cuuint32_t box[2] = {b0, b1}, es[2] = {1, 1};
    enc(m, dt, 2, (void*)p, dim, str, box, es, CU_TENSOR_MAP_INTERLEAVE_NONE, sw, CU_TENSOR_MAP_L2_PROMOTION_L2_128B, CU_TENSOR_MAP_FLOAT_OOB_FILL_NONE);
}

#define FORCE_SPLIT 0

extern "C" void kernel_launch(void* const* d_in, const int* in_sizes, int n_in, void* d_out, int out_size) {
    const bf16* x = (const bf16*)d_in[0];
    const bf16* wqkv = (const bf16*)d_in[1];
    const bf16* wo = (const bf16*)d_in[2];
    const bf16* wg = (const bf16*)d_in[4];
    const bf16* wu = (const bf16*)d_in[5];
    const bf16* wd = (const bf16*)d_in[6];

    EncodeFn enc = nullptr;
    cudaDriverEntryPointQueryResult qr;
    cudaGetDriverEntryPoint("cuTensorMapEncodeTiled", (void**)&enc, cudaEnableDefault, &qr);
    void *p_o, *p_h, *p_act;
    cudaGetSymbolAddress(&p_o, g_o);
    cudaGetSymbolAddress(&p_h, g_h);
    cudaGetSymbolAddress(&p_act, g_act);
    Maps m;
    const CUtensorMapDataType BF = CU_TENSOR_MAP_DATA_TYPE_BFLOAT16, U64 = CU_TENSOR_MAP_DATA_TYPE_UINT64;
    enc2d(enc, &m.x, BF, x, D_, S_, D_ * 2, 64, 128, CU_TENSOR_MAP_SWIZZLE_128B);
    enc2d(enc, &m.wqkv, BF, wqkv, 1920, D_, 1920 * 2, 64, 64, CU_TENSOR_MAP_SWIZZLE_128B);
    enc2d(enc, &m.wo, BF, wo, D_, D_, D_ * 2, 64, 64, CU_TENSOR_MAP_SWIZZLE_128B);
    enc2d(enc, &m.o, U64, p_o, 1280, S_ / 8, 10240, 128, 10, CU_TENSOR_MAP_SWIZZLE_NONE);
    enc2d(enc, &m.h, BF, p_h, D_, S_, D_ * 2, 64, 128, CU_TENSOR_MAP_SWIZZLE_128B);
    enc2d(enc, &m.wg, BF, wg, F_, D_, F_ * 2, 64, 64, CU_TENSOR_MAP_SWIZZLE_128B);
    enc2d(enc, &m.wu, BF, wu, F_, D_, F_ * 2, 64, 64, CU_TENSOR_MAP_SWIZZLE_128B);
    enc2d(enc, &m.act, U64, p_act, 3072, S_ / 8, 24576, 128, 10, CU_TENSOR_MAP_SWIZZLE_NONE);
    enc2d(enc, &m.wd, BF, wd, D_, F_, D_ * 2, 64, 64, CU_TENSOR_MAP_SWIZZLE_128B);

    cudaFuncSetAttribute(block_kernel, cudaFuncAttributeMaxDynamicSharedMemorySize, SM_TOTAL);
    cudaLaunchConfig_t cfg = {};
    cfg.gridDim = NCTA; cfg.blockDim = NTHR; cfg.dynamicSmemBytes = SM_TOTAL;
    cudaLaunchAttribute at;
    at.id = cudaLaunchAttributeClusterDimension; at.val.clusterDim.x = 2; at.val.clusterDim.y = 1; at.val.clusterDim.z = 1;
    cfg.attrs = &at; cfg.numAttrs = 1;
    int ncl = 0;
    cudaOccupancyMaxActiveClusters(&ncl, block_kernel, &cfg);
    if (2 * ncl >= NCTA && !FORCE_SPLIT) {
        block_kernel<<<NCTA, NTHR, SM_TOTAL>>>(m, x, wqkv, wo, wg, wu, wd, (bf16*)d_out, PH_ALL);
    } else {
        for (int ph = PH_PRE; ph <= PH_DN; ph <<= 1) block_kernel<<<NCTA, NTHR, SM_TOTAL>>>(m, x, wqkv, wo, wg, wu, wd, (bf16*)d_out, ph);
    }
}
```

```cpp
#include <cuda_runtime.h>
#include <cuda_bf16.h>
#include <cuda.h>
#include <stdint.h>

typedef __nv_bfloat16 bf16;

constexpr int S_ = 2048, D_ = 640, F_ = 1536;
constexpr int NCTA = 132, NTHR = 640;
constexpr int NE = 5;
constexpr int NDS = 4;
constexpr uint32_t POLYMASK = 0x7777;

__device__ __align__(1024) uint8_t g_qkv[64 * 196608];
__device__ __align__(1024) uint8_t g_o[S_ * D_ * 2];
__device__ __align__(1024) bf16 g_h[S_ * D_];
__device__ __align__(1024) uint8_t g_act[S_ * F_ * 2];
__device__ __align__(128) uint2 g_stat1[S_];
__device__ __align__(128) float2 g_part2[S_ * 10];
__device__ __align__(128) float g_cs2[2 * F_];
__device__ __align__(128) float g_nrm[2 * 96 * 128];
__device__ __align__(128) uint32_t g_cs1[2 * 1920];
enum { C_CS2 = 1, C_DONE = 2, C_EPOCH = 3, C_QKV = 4  , C_ATT = 36  , C_H = 52  , C_ACT = 78  , C_ST2 = 126  , C_NUM = 152 };
__device__ __align__(128) uint32_t g_cnt[C_NUM * 32];

enum { PH_PRE = 1, PH_QKV = 2, PH_ATT = 4, PH_OPJ = 8, PH_UP = 16, PH_DN = 32, PH_ALL = 63 };

struct Maps { CUtensorMap x, wqkv, wqkv5, wo, o, h, wg, wu, act, wd; };

constexpr uint32_t SM_RING = 163840;
constexpr uint32_t SM_CS = 229376;
constexpr uint32_t SM_BAR = SM_CS + 2560;
constexpr uint32_t SM_VER = SM_RING + 49152;
constexpr uint32_t SM_TAG = SM_BAR + 8 * 31;
constexpr uint32_t SM_TOTAL = SM_BAR + 512;
enum { B_RF = 0  , B_RA = 8  , B_AF = 18  , B_TF = 26  , B_SOLO = 33, B_TURN = 34  , B_DEP1 = 37,
       B_HE = 38, B_VER = 39, B_OPE = 40,
       B_TE = 41  , B_PART1 = 48  , B_RE = 49  , B_FREE3 = 57, B_STG = 58, B_FREE0 = 59,
       B_STAT = 60  , B_STAT2 = 61  , B_FREE1 = 62, B_HALF1 = 63  , B_NUM = 64 };

__device__ __forceinline__ void wg_fence() { asm volatile("wgmma.fence.sync.aligned;" ::: "memory"); }
__device__ __forceinline__ void wg_commit() { asm volatile("wgmma.commit_group.sync.aligned;" ::: "memory"); }
template <int N> __device__ __forceinline__ void wg_wait() { asm volatile("wgmma.wait_group.sync.aligned %0;" ::"n"(N) : "memory"); }
template <int N> __device__ __forceinline__ void pin(float (&a)[N]) {
#pragma unroll
    for (int i = 0; i < N; i++) asm volatile("" : "+f"(a[i])::"memory");
}
template <int N> __device__ __forceinline__ void pin(uint32_t (&a)[N]) {
#pragma unroll
    for (int i = 0; i < N; i++) asm volatile("" : "+r"(a[i])::"memory");
}
__device__ __forceinline__ uint64_t mkdesc(uint32_t addr, uint32_t lbo, uint32_t sbo, uint32_t swz) {
    return (uint64_t)((addr & 0x3FFFF) >> 4) | ((uint64_t)(lbo >> 4) << 16) | ((uint64_t)(sbo >> 4) << 32) | ((uint64_t)swz << 62);
}
__device__ __forceinline__ void mbar_init(uint32_t bar, uint32_t cnt) { asm volatile("mbarrier.init.shared::cta.b64 [%0], %1;" ::"r"(bar), "r"(cnt) : "memory"); }
__device__ __forceinline__ void mbar_expect_tx(uint32_t bar, uint32_t bytes) { asm volatile("mbarrier.arrive.expect_tx.shared::cta.b64 _, [%0], %1;" ::"r"(bar), "r"(bytes) : "memory"); }
__device__ __forceinline__ void mbar_arrive(uint32_t bar) { asm volatile("mbarrier.arrive.shared::cta.b64 _, [%0];" ::"r"(bar) : "memory"); }
__device__ __forceinline__ void mbar_wait(uint32_t bar, uint32_t parity) {
    asm volatile("{\n.reg .pred p;\nW%=:\nmbarrier.try_wait.parity.shared::cta.b64 p, [%0], %1, %2;\n@!p bra W%=;\n}\n" ::"r"(bar), "r"(parity), "r"(10000) : "memory");
}
__device__ __forceinline__ void bulk_g2s(uint32_t dst, const void* src, uint32_t bytes, uint32_t bar) {
    asm volatile("cp.async.bulk.shared::cluster.global.mbarrier::complete_tx::bytes [%0], [%1], %2, [%3];" ::"r"(dst), "l"(src), "r"(bytes), "r"(bar) : "memory");
}
__device__ __forceinline__ void tma2d(uint32_t dst, const CUtensorMap* m, int c0, int c1, uint32_t bar) {
    asm volatile("cp.async.bulk.tensor.2d.shared::cluster.global.mbarrier::complete_tx::bytes [%0], [%1, {%3, %4}], [%2];" ::"r"(dst), "l"(m), "r"(bar), "r"(c0), "r"(c1) : "memory");
}
__device__ __forceinline__ void tma3d(uint32_t dst, const CUtensorMap* m, int c0, int c1, int c2, uint32_t bar) {
    asm volatile("cp.async.bulk.tensor.3d.shared::cluster.global.mbarrier::complete_tx::bytes [%0], [%1, {%3, %4, %5}], [%2];" ::"r"(dst), "l"(m), "r"(bar), "r"(c0), "r"(c1), "r"(c2) : "memory");
}
__device__ __forceinline__ void prefetch_map(const CUtensorMap* m) { asm volatile("prefetch.tensormap [%0];" ::"l"(m) : "memory"); }
__device__ __forceinline__ void l2_prefetch(const void* p, uint32_t bytes) { asm volatile("cp.async.bulk.prefetch.L2.global [%0], %1;" ::"l"(p), "r"(bytes) : "memory"); }
__device__ __forceinline__ void fence_async_global() { asm volatile("fence.proxy.async.global;" ::: "memory"); }
__device__ __forceinline__ void bar_sync(int id, int n) { asm volatile("bar.sync %0, %1;" ::"r"(id), "r"(n) : "memory"); }
__device__ __forceinline__ void publish(int pair) { asm volatile("bar.arrive %0, 288;" ::"r"(1 + pair) : "memory"); }
__device__ __forceinline__ void cnt_signal(int c) { asm volatile("red.release.gpu.global.add.u32 [%0], 1;" ::"l"(g_cnt + c * 32) : "memory"); }
__device__ __forceinline__ void cnt_wait(bool active, int c, uint32_t target) {
    if (active) {
        const uint32_t* p = g_cnt + c * 32;
#pragma unroll 1
        for (int it = 0; it < 1000000; it++) {
            uint32_t v;
            asm volatile("ld.relaxed.gpu.global.u32 %0, [%1];" : "=r"(v) : "l"(p) : "memory");
            if ((int)(v - target) >= 0) break;
        }
        asm volatile("fence.acquire.gpu;" ::: "memory");
    }
    __syncwarp();
}
__device__ __forceinline__ bool elect_one() {
    uint32_t p;
    asm volatile("{\n.reg .pred P;\nelect.sync _|P, 0xffffffff;\nselp.b32 %0, 1, 0, P;\n}\n" : "=r"(p));
    return p != 0;
}
__device__ __forceinline__ uint32_t pack_bf16(float lo, float hi) {
    uint32_t r;
    asm("cvt.rn.bf16x2.f32 %0, %1, %2;" : "=r"(r) : "f"(hi), "f"(lo));
    return r;
}
__device__ __forceinline__ uint32_t add_bf16x2(uint32_t a, uint32_t b) {
    uint32_t r;
    asm("add.rn.bf16x2 %0, %1, %2;" : "=r"(r) : "r"(a), "r"(b));
    return r;
}
__device__ __forceinline__ float bf_lo(uint32_t v) { return __uint_as_float(v << 16); }
__device__ __forceinline__ float bf_hi(uint32_t v) { return __uint_as_float(v & 0xFFFF0000u); }
__device__ __forceinline__ float rbf(float v) { return __bfloat162float(__float2bfloat16_rn(v)); }
__device__ __forceinline__ float ln_rstd(float var) {
    float s;
    asm("sqrt.approx.f32 %0, %1;" : "=f"(s) : "f"(rbf(rbf(var) + 1e-5f)));
    return __fdividef(1.f, rbf(s));
}
__device__ __forceinline__ float ex2(float x) {
    float r;
    asm("ex2.approx.ftz.f32 %0, %1;" : "=f"(r) : "f"(x));
    return r;
}

__device__ __forceinline__ void wgmma_ss_n8_ta(float (&d)[4], uint64_t da, uint64_t db) {
    asm volatile(
        "wgmma.mma_async.sync.aligned.m64n8k16.f32.bf16.bf16 {"
        "%0, %1, %2, %3"
        "}, %4, %5, 1, 1, 1, 1, 0;\n"
        :
        "+f"(d[0]), "+f"(d[1]), "+f"(d[2]), "+f"(d[3])
        : "l"(da), "l"(db));
}
template <int SCALE_D>
__device__ __forceinline__ void wgmma_rs_n128(float (&d)[64], uint32_t a0, uint32_t a1, uint32_t a2, uint32_t a3, uint64_t db) {
    asm volatile(
        "wgmma.mma_async.sync.aligned.m64n128k16.f32.bf16.bf16 {"
        "%0, %1, %2, %3, %4, %5, %6, %7, %8, %9, %10, %11, %12, %13, %14, %15, "
        "%16, %17, %18, %19, %20, %21, %22, %23, %24, %25, %26, %27, %28, %29, %30, %31, "
        "%32, %33, %34, %35, %36, %37, %38, %39, %40, %41, %42, %43, %44, %45, %46, %47, "
        "%48, %49, %50, %51, %52, %53, %54, %55, %56, %57, %58, %59, %60, %61, %62, %63"
        "}, {%64, %65, %66, %67}, %68, %69, 1, 1, 0;\n"
        :
        "+f"(d[0]), "+f"(d[1]), "+f"(d[2]), "+f"(d[3]), "+f"(d[4]), "+f"(d[5]), "+f"(d[6]), "+f"(d[7]),
        "+f"(d[8]), "+f"(d[9]), "+f"(d[10]), "+f"(d[11]), "+f"(d[12]), "+f"(d[13]), "+f"(d[14]), "+f"(d[15]),
        "+f"(d[16]), "+f"(d[17]), "+f"(d[18]), "+f"(d[19]), "+f"(d[20]), "+f"(d[21]), "+f"(d[22]), "+f"(d[23]),
        "+f"(d[24]), "+f"(d[25]), "+f"(d[26]), "+f"(d[27]), "+f"(d[28]), "+f"(d[29]), "+f"(d[30]), "+f"(d[31]),
        "+f"(d[32]), "+f"(d[33]), "+f"(d[34]), "+f"(d[35]), "+f"(d[36]), "+f"(d[37]), "+f"(d[38]), "+f"(d[39]),
        "+f"(d[40]), "+f"(d[41]), "+f"(d[42]), "+f"(d[43]), "+f"(d[44]), "+f"(d[45]), "+f"(d[46]), "+f"(d[47]),
        "+f"(d[48]), "+f"(d[49]), "+f"(d[50]), "+f"(d[51]), "+f"(d[52]), "+f"(d[53]), "+f"(d[54]), "+f"(d[55]),
        "+f"(d[56]), "+f"(d[57]), "+f"(d[58]), "+f"(d[59]), "+f"(d[60]), "+f"(d[61]), "+f"(d[62]), "+f"(d[63])
        : "r"(a0), "r"(a1), "r"(a2), "r"(a3), "l"(db), "n"(SCALE_D));
}
template <int SCALE_D>
__device__ __forceinline__ void wgmma_rs_n24_tb(float (&d)[12], uint32_t a0, uint32_t a1, uint32_t a2, uint32_t a3, uint64_t db) {
    asm volatile(
        "wgmma.mma_async.sync.aligned.m64n24k16.f32.bf16.bf16 {"
        "%0, %1, %2, %3, %4, %5, %6, %7, %8, %9, %10, %11"
        "}, {%12, %13, %14, %15}, %16, %17, 1, 1, 1;\n"
        :
        "+f"(d[0]), "+f"(d[1]), "+f"(d[2]), "+f"(d[3]), "+f"(d[4]), "+f"(d[5]), "+f"(d[6]), "+f"(d[7]),
        "+f"(d[8]), "+f"(d[9]), "+f"(d[10]), "+f"(d[11])
        : "r"(a0), "r"(a1), "r"(a2), "r"(a3), "l"(db), "n"(SCALE_D));
}
__device__ __forceinline__ void wgmma_ss_n128_tb(float (&d)[64], uint64_t da, uint64_t db) {
    asm volatile(
        "wgmma.mma_async.sync.aligned.m64n128k16.f32.bf16.bf16 {"
        "%0, %1, %2, %3, %4, %5, %6, %7, %8, %9, %10, %11, %12, %13, %14, %15, "
        "%16, %17, %18, %19, %20, %21, %22, %23, %24, %25, %26, %27, %28, %29, %30, %31, "
        "%32, %33, %34, %35, %36, %37, %38, %39, %40, %41, %42, %43, %44, %45, %46, %47, "
        "%48, %49, %50, %51, %52, %53, %54, %55, %56, %57, %58, %59, %60, %61, %62, %63"
        "}, %64, %65, 1, 1, 1, 0, 1;\n"
        :
        "+f"(d[0]), "+f"(d[1]), "+f"(d[2]), "+f"(d[3]), "+f"(d[4]), "+f"(d[5]), "+f"(d[6]), "+f"(d[7]),
        "+f"(d[8]), "+f"(d[9]), "+f"(d[10]), "+f"(d[11]), "+f"(d[12]), "+f"(d[13]), "+f"(d[14]), "+f"(d[15]),
        "+f"(d[16]), "+f"(d[17]), "+f"(d[18]), "+f"(d[19]), "+f"(d[20]), "+f"(d[21]), "+f"(d[22]), "+f"(d[23]),
        "+f"(d[24]), "+f"(d[25]), "+f"(d[26]), "+f"(d[27]), "+f"(d[28]), "+f"(d[29]), "+f"(d[30]), "+f"(d[31]),
        "+f"(d[32]), "+f"(d[33]), "+f"(d[34]), "+f"(d[35]), "+f"(d[36]), "+f"(d[37]), "+f"(d[38]), "+f"(d[39]),
        "+f"(d[40]), "+f"(d[41]), "+f"(d[42]), "+f"(d[43]), "+f"(d[44]), "+f"(d[45]), "+f"(d[46]), "+f"(d[47]),
        "+f"(d[48]), "+f"(d[49]), "+f"(d[50]), "+f"(d[51]), "+f"(d[52]), "+f"(d[53]), "+f"(d[54]), "+f"(d[55]),
        "+f"(d[56]), "+f"(d[57]), "+f"(d[58]), "+f"(d[59]), "+f"(d[60]), "+f"(d[61]), "+f"(d[62]), "+f"(d[63])
        : "l"(da), "l"(db));
}
__device__ __forceinline__ void wgmma_ss_n80_ta(float (&d)[40], uint64_t da, uint64_t db) {
    asm volatile(
        "wgmma.mma_async.sync.aligned.m64n80k16.f32.bf16.bf16 {"
        "%0, %1, %2, %3, %4, %5, %6, %7, %8, %9, %10, %11, %12, %13, %14, %15, "
        "%16, %17, %18, %19, %20, %21, %22, %23, %24, %25, %26, %27, %28, %29, %30, %31, "
        "%32, %33, %34, %35, %36, %37, %38, %39"
        "}, %40, %41, 1, 1, 1, 1, 0;\n"
        :
        "+f"(d[0]), "+f"(d[1]), "+f"(d[2]), "+f"(d[3]), "+f"(d[4]), "+f"(d[5]), "+f"(d[6]), "+f"(d[7]),
        "+f"(d[8]), "+f"(d[9]), "+f"(d[10]), "+f"(d[11]), "+f"(d[12]), "+f"(d[13]), "+f"(d[14]), "+f"(d[15]),
        "+f"(d[16]), "+f"(d[17]), "+f"(d[18]), "+f"(d[19]), "+f"(d[20]), "+f"(d[21]), "+f"(d[22]), "+f"(d[23]),
        "+f"(d[24]), "+f"(d[25]), "+f"(d[26]), "+f"(d[27]), "+f"(d[28]), "+f"(d[29]), "+f"(d[30]), "+f"(d[31]),
        "+f"(d[32]), "+f"(d[33]), "+f"(d[34]), "+f"(d[35]), "+f"(d[36]), "+f"(d[37]), "+f"(d[38]), "+f"(d[39])
        : "l"(da), "l"(db));
}
__device__ __forceinline__ void wgmma_ss_n80_tatb(float (&d)[40], uint64_t da, uint64_t db) {
    asm volatile(
        "wgmma.mma_async.sync.aligned.m64n80k16.f32.bf16.bf16 {"
        "%0, %1, %2, %3, %4, %5, %6, %7, %8, %9, %10, %11, %12, %13, %14, %15, "
        "%16, %17, %18, %19, %20, %21, %22, %23, %24, %25, %26, %27, %28, %29, %30, %31, "
        "%32, %33, %34, %35, %36, %37, %38, %39"
        "}, %40, %41, 1, 1, 1, 1, 1;\n"
        :
        "+f"(d[0]), "+f"(d[1]), "+f"(d[2]), "+f"(d[3]), "+f"(d[4]), "+f"(d[5]), "+f"(d[6]), "+f"(d[7]),
        "+f"(d[8]), "+f"(d[9]), "+f"(d[10]), "+f"(d[11]), "+f"(d[12]), "+f"(d[13]), "+f"(d[14]), "+f"(d[15]),
        "+f"(d[16]), "+f"(d[17]), "+f"(d[18]), "+f"(d[19]), "+f"(d[20]), "+f"(d[21]), "+f"(d[22]), "+f"(d[23]),
        "+f"(d[24]), "+f"(d[25]), "+f"(d[26]), "+f"(d[27]), "+f"(d[28]), "+f"(d[29]), "+f"(d[30]), "+f"(d[31]),
        "+f"(d[32]), "+f"(d[33]), "+f"(d[34]), "+f"(d[35]), "+f"(d[36]), "+f"(d[37]), "+f"(d[38]), "+f"(d[39])
        : "l"(da), "l"(db));
}


__device__ __forceinline__ uint32_t exp2_fma(float t0, float t1, uint32_t minus1) {
    uint32_t u = __byte_perm(__float_as_uint(t0), __float_as_uint(t1), 0x6521);
    uint32_t y, e, r;
    asm("lop3.b32 %0, %1, %2, %3, 0xEA;" : "=r"(y) : "r"(u), "r"(0x007E007E), "r"(0x9F809F80));
    asm("mad.lo.u32 %0, %1, %2, %3;" : "=r"(e) : "r"(y), "r"(minus1), "r"(u));
    asm("fma.rn.bf16x2 %0, %1, %2, %3;" : "=r"(r) : "r"(u), "r"(y), "r"(e));
    return r;
}
__device__ __forceinline__ uint32_t exp2_mufu(float t0, float t1) { return pack_bf16(ex2(t0), ex2(t1)); }

template <int T0, int T1>
__device__ __forceinline__ void softmax_pv(float (&s)[64], uint32_t (&p)[32], float (&o)[12], uint64_t dv, uint32_t minus1) {
#pragma unroll
    for (int t = T0; t < T1; t++) {
        if ((POLYMASK >> t) & 1) {
            p[2 * t] = exp2_fma(s[4 * t], s[4 * t + 1], minus1);
            p[2 * t + 1] = exp2_fma(s[4 * t + 2], s[4 * t + 3], minus1);
        } else {
            p[2 * t] = exp2_mufu(s[4 * t], s[4 * t + 1]);
            p[2 * t + 1] = exp2_mufu(s[4 * t + 2], s[4 * t + 3]);
        }
    }
#pragma unroll
    for (int t = 2 * T0; t < 2 * T1; t++) asm volatile("" : "+r"(p[t])::"memory");
    wg_fence();
#pragma unroll
    for (int kk = T0 / 2; kk < T1 / 2; kk++) wgmma_rs_n24_tb<1>(o, p[4 * kk], p[4 * kk + 1], p[4 * kk + 2], p[4 * kk + 3], dv + kk * 48);
}

__device__ __forceinline__ void load_q(uint32_t (&q)[6], int head, int row0, int lane) {
    const uint8_t* qg = g_qkv + (size_t)head * 196608 + (row0 >> 7) * 12288 + ((row0 & 127) >> 3) * 384 + lane * 4;
    q[0] = __ldcg((const uint32_t*)qg); q[1] = __ldcg((const uint32_t*)(qg + 384));
    q[2] = __ldcg((const uint32_t*)(qg + 128)); q[3] = __ldcg((const uint32_t*)(qg + 512));
    q[4] = __ldcg((const uint32_t*)(qg + 256)); q[5] = __ldcg((const uint32_t*)(qg + 640));
}
__device__ __forceinline__ void attn_store(float (&o)[12], int head, int rb, int warp, int lane) {
    const int g = lane >> 2;
    const float l0 = __shfl_sync(~0u, o[8], (lane & ~3) | 2), l1 = __shfl_sync(~0u, o[10], (lane & ~3) | 2);
    const float r0 = __fdividef(1.f, l0), r1 = __fdividef(1.f, l1);
    uint8_t* og = g_o + (size_t)(rb * 8 + (warp & 3) * 2) * 10240 + head * 320 + lane * 4;
#pragma unroll
    for (int t = 0; t < 3; t++) {
        uint32_t a = pack_bf16(o[4 * t] * r0, o[4 * t + 1] * r0), b = pack_bf16(o[4 * t + 2] * r1, o[4 * t + 3] * r1);
        asm volatile("movmatrix.sync.aligned.m8n8.trans.b16 %0, %0;" : "+r"(a));
        asm volatile("movmatrix.sync.aligned.m8n8.trans.b16 %0, %0;" : "+r"(b));
        if (t < 2 || g < 4) {
            *(uint32_t*)(og + t * 128) = a;
            *(uint32_t*)(og + t * 128 + 10240) = b;
        }
    }
    publish(warp >> 3);
}

__device__ __forceinline__ void attention_general(uint32_t sb, int head, int qb, bool opj) {
    const int tid = threadIdx.x, warp = __shfl_sync(~0u, tid >> 5, 0), wg = warp >> 2, lane = tid & 31, c = lane & 3;
    const uint32_t bar = sb + SM_BAR;
    const uint64_t dK0 = mkdesc(sb, 128, 384, 0), dK1 = mkdesc(sb + 256, 0, 384, 0), dV = mkdesc(sb + 6144, 384, 128, 0);
#pragma unroll 1
    for (int blk = 0; blk < 2; blk++) {
        const int rb = blk * 16 + qb * 4 + wg;
        uint32_t q[6];
        load_q(q, head, rb * 64 + (warp & 3) * 16, lane);
        if (c >= 2) q[4] = q[5] = 0;
        pin(q);
        float o[12], s[64];
        uint32_t p[32];
#pragma unroll
        for (int i = 0; i < 12; i++) o[i] = 0.f;
        float m0 = -INFINITY, m1 = -INFINITY;
#pragma unroll 1
        for (int j = 0; j < 16; j++) {
            wg_fence();
            wgmma_rs_n128<0>(s, q[0], q[1], q[2], q[3], dK0 + j * 768);
            wgmma_rs_n128<1>(s, q[4], q[5], 0u, 0u, dK1 + j * 768);
            wg_commit();
            wg_wait<0>();
            pin(s);
            float n0 = m0, n1 = m1;
#pragma unroll
            for (int t = 0; t < 16; t++) {
                n0 = fmaxf(n0, fmaxf(s[4 * t], s[4 * t + 1]));
                n1 = fmaxf(n1, fmaxf(s[4 * t + 2], s[4 * t + 3]));
            }
#pragma unroll
            for (int m = 1; m < 4; m <<= 1) { n0 = fmaxf(n0, __shfl_xor_sync(~0u, n0, m)); n1 = fmaxf(n1, __shfl_xor_sync(~0u, n1, m)); }
            const float f0 = ex2(m0 - n0), f1 = ex2(m1 - n1);
            m0 = n0; m1 = n1;
#pragma unroll
            for (int t = 0; t < 3; t++) { o[4 * t] *= f0; o[4 * t + 1] *= f0; o[4 * t + 2] *= f1; o[4 * t + 3] *= f1; }
#pragma unroll
            for (int t = 0; t < 16; t++) {
                p[2 * t] = exp2_mufu(s[4 * t] - m0, s[4 * t + 1] - m0);
                p[2 * t + 1] = exp2_mufu(s[4 * t + 2] - m1, s[4 * t + 3] - m1);
            }
            pin(p);
            pin(o);
            wg_fence();
#pragma unroll
            for (int kk = 0; kk < 8; kk++) wgmma_rs_n24_tb<1>(o, p[4 * kk], p[4 * kk + 1], p[4 * kk + 2], p[4 * kk + 3], dV + j * 768 + kk * 48);
            wg_commit();
            wg_wait<0>();
            pin(o);
        }
        if (blk == 1 && lane == 0) { mbar_arrive(bar + 8 * B_PART1); mbar_arrive(bar + 8 * B_HALF1); mbar_arrive(bar + 8 * B_FREE1); }
        if (blk == 1 && opj) asm volatile("bar.arrive 0, 544;" ::: "memory");
        attn_store(o, head, rb, warp, lane);
    }
}

__device__ __forceinline__ void helper_pre(float* red, int hi, const bf16* __restrict__ wo, const bf16* __restrict__ wgate,
                                        const bf16* __restrict__ wup, const bf16* __restrict__ wdown) {
    const int tid = threadIdx.x;
    const bf16* w = (hi >> 1) ? wup : wgate;
    const int co = tid % 96, rg = tid / 96;
    if (tid < 480) {
        const uint4* wp = (const uint4*)(w + (size_t)(rg * 128) * F_ + (hi & 1) * 768) + co;
        float a[8];
#pragma unroll
        for (int q = 0; q < 8; q++) a[q] = 0.f;
#pragma unroll 1
        for (int r = 0; r < 128; r += 16) {
            uint4 u[16];
#pragma unroll
            for (int i = 0; i < 16; i++) u[i] = __ldg(wp + (size_t)(r + i) * (F_ / 8));
#pragma unroll
            for (int i = 0; i < 16; i++) {
                a[0] += bf_lo(u[i].x); a[1] += bf_hi(u[i].x); a[2] += bf_lo(u[i].y); a[3] += bf_hi(u[i].y);
                a[4] += bf_lo(u[i].z); a[5] += bf_hi(u[i].z); a[6] += bf_lo(u[i].w); a[7] += bf_hi(u[i].w);
            }
        }
#pragma unroll
        for (int q = 0; q < 8; q++) red[rg * 768 + co * 8 + q] = a[q];
    }
    bar_sync(5, 512);
    if (tid >= 480 && tid < 496) {
        const int i = (tid - 480) + hi * 16;
        l2_prefetch((const uint8_t*)wo + i * 12800, 12800);
        l2_prefetch((const uint8_t*)wdown + i * 30720, 30720);
    }
#pragma unroll 1
    for (int i = tid; i < 768; i += 512)
        g_cs2[(hi >> 1) * F_ + (hi & 1) * 768 + i] = red[i] + red[768 + i] + red[1536 + i] + red[2304 + i] + red[3072 + i];
    bar_sync(5, 512);
    if (tid == 0) cnt_signal(C_CS2);
}

template <int R5>
__device__ __forceinline__ void qkv_store(const float (&acc)[64], uint32_t (&w0)[20], uint32_t (&w1)[20], const uint8_t* smem, int kind, int rt, int warp, int lane) {
    const int g = lane >> 2, c = lane & 3, rl = (warp & 7) * 16;
    const float* s_cs = (const float*)(smem + SM_CS);
    const float2* s_st = (const float2*)(smem + SM_CS + 512) + (warp >> 3) * 128;
    const float2 st0 = s_st[rl + g], st1 = s_st[rl + g + 8];
    constexpr float QSCALE = 0.22360679774997896f * 1.4426950408889634f;
    const float r0 = st0.y * (kind ? 1.f : QSCALE), r1 = st1.y * (kind ? 1.f : QSCALE);
    const uint32_t pad0 = (c & 1) ? 0u : kind == 2 ? 0x00003F80u : (((POLYMASK >> (rl >> 3)) & 1) ? 0x3F803F80u : 0u);
    const uint32_t pad1 = (c & 1) ? 0u : kind == 2 ? 0x00003F80u : (((POLYMASK >> ((rl >> 3) + 1)) & 1) ? 0x3F803F80u : 0u);
    uint8_t* base = g_qkv + (size_t)((kind ? 32 : 0) + R5 * 6) * 196608 + (kind == 2 ? 6144 : 0) + rt * 12288 + (rl >> 3) * 384 + g * 16;
    uint8_t* pa = base + 4 * c;
    uint8_t* pb = base + 196608 + 4 * (c ^ 2);
    const bool lo = c < 2;
#pragma unroll
    for (int hp = 0; hp < 4; hp++) {
        uint32_t* u0 = w0 + hp * 5;
        uint32_t* u1 = w1 + hp * 5;
        auto ok = [&](int jj) { return hp * 5 + jj >= R5 && hp * 5 + jj < R5 + 16; };
#pragma unroll
        for (int jj = 0; jj < 5; jj++) {
            u0[jj] = u1[jj] = 0;
            if (ok(jj)) {
                const int j = hp * 5 + jj - R5;
                const float2 cs = *(const float2*)(s_cs + 8 * j + 2 * c);
                u0[jj] = pack_bf16(r0 * fmaf(-st0.x, cs.x, acc[4 * j]), r0 * fmaf(-st0.x, cs.y, acc[4 * j + 1]));
                u1[jj] = pack_bf16(r1 * fmaf(-st1.x, cs.x, acc[4 * j + 2]), r1 * fmaf(-st1.x, cs.y, acc[4 * j + 3]));
            }
        }
        auto st2 = [&](uint8_t* p, uint32_t a, uint32_t e, bool v) { if (v) { *(uint32_t*)p = a; *(uint32_t*)(p + 384) = e; } };
        st2(pa + hp * 393216, u0[0], u1[0], ok(0));
        st2(pa + hp * 393216 + 128, u0[1], u1[1], ok(1));
        st2(pa + hp * 393216 + 256, lo ? u0[2] : pad0, lo ? u1[2] : pad1, ok(2));
        st2(pb + hp * 393216, lo ? u0[3] : u0[2], lo ? u1[3] : u1[2], lo ? ok(3) : ok(2));
        st2(pb + hp * 393216 + 128, lo ? u0[4] : u0[3], lo ? u1[4] : u1[3], lo ? ok(4) : ok(3));
        st2(pb + hp * 393216 + 256, lo ? pad0 : u0[4], lo ? pad1 : u1[4], ok(4));
    }
    asm volatile("bar.arrive %0, 288;  // %1" ::"r"(1 + (warp >> 3)), "n"(R5) : "memory");
}
__device__ __forceinline__ void qkv_norms(const uint32_t (&w0)[20], const uint32_t (&w1)[20], const uint8_t* smem, int kind, int R5, int rt, int warp, int lane) {
    const int g = lane >> 2, c = lane & 3;
    const bool lo = c < 2;
    const uint32_t tag = *(const volatile uint32_t*)(smem + SM_TAG);
    auto sq3 = [](uint32_t a, uint32_t e, uint32_t f) {
        uint32_t s;
        asm("{\n.reg .b32 t;\nmul.bf16x2 t, %1, %1;\nfma.rn.bf16x2 t, %2, %2, t;\nfma.rn.bf16x2 %0, %3, %3, t;\n}\n" : "=r"(s) : "r"(a), "r"(e), "r"(f));
        return s;
    };
    auto max2 = [](uint32_t a, uint32_t e) { uint32_t s; asm("max.NaN.bf16x2 %0, %1, %2;" : "=r"(s) : "r"(a), "r"(e)); return s; };
    uint32_t n[8];
#pragma unroll
    for (int hp = 0; hp < 4; hp++) {
        const uint32_t* u0 = w0 + hp * 5;
        const uint32_t* u1 = w1 + hp * 5;
        const uint32_t a0 = sq3(u0[0], u0[1], lo ? u0[2] : 0u), a1 = sq3(u1[0], u1[1], lo ? u1[2] : 0u);
        const uint32_t b0 = sq3(u0[3], u0[4], lo ? 0u : u0[2]), b1 = sq3(u1[3], u1[4], lo ? 0u : u1[2]);
        n[2 * hp] = add_bf16x2(__byte_perm(a0, a1, 0x5410), __byte_perm(a0, a1, 0x7632));
        n[2 * hp + 1] = add_bf16x2(__byte_perm(b0, b1, 0x5410), __byte_perm(b0, b1, 0x7632));
    }
#pragma unroll
    for (int q = 0; q < 4; q++) n[q] = add_bf16x2(lo ? n[q] : n[q + 4], __shfl_xor_sync(~0u, lo ? n[q + 4] : n[q], 2));
#pragma unroll
    for (int q = 0; q < 2; q++) n[q] = add_bf16x2((c & 1) ? n[q + 2] : n[q], __shfl_xor_sync(~0u, (c & 1) ? n[q] : n[q + 2], 1));
    uint32_t mx = max2(__byte_perm(n[0], n[1], 0x5410), __byte_perm(n[0], n[1], 0x7632));
#pragma unroll
    for (int m = 4; m < 32; m <<= 1) mx = max2(mx, __shfl_xor_sync(~0u, mx, m));
    const bool have = c == 0 ? (g || R5 <= 2) : c == 3 ? (!g || R5 >= 2) : true;
    const int part = c == 0 && (g ? R5 > 2 : R5 > 0);
    if (g < 2 && have)
        g_nrm[(part * 96 + kind * 32 + R5 * 6 + c * 2 + g) * 128 + rt * 8 + (warp & 7)] = __uint_as_float(((g ? mx : mx << 16) & 0x7FFF0000u) | tag);
}

__device__ __forceinline__ uint32_t wo_off(int i) { return i < 4 ? 196608 + i * 8192 : i < 9 ? 102400 - 4 * 8192 + i * 8192 : 147456; }

template <bool UP>
__device__ __forceinline__ void rgemm_load_ring(uint32_t sb, const Maps& maps, int pos, int kb, int i) {
    const uint32_t fb = sb + SM_BAR + 8 * (B_RF + 4 * UP + (i & 3)), dst = sb + SM_RING + (i & 3) * 16384;
    mbar_expect_tx(fb, 16384);
    if (UP) {
        tma2d(dst, &maps.wg, pos, kb * 64, fb);
        tma2d(dst + 8192, &maps.wu, pos, kb * 64, fb);
    } else {
        tma2d(dst, &maps.x, kb * 64, pos, fb);
        tma2d(dst + 8192, &maps.x, kb * 64 + (i < 10 ? 0 : 64), pos + (i < 10 ? 64 : 0), fb);
    }
}
template <bool UP>
__device__ __forceinline__ void rgemm_load_res(uint32_t sb, const Maps& maps, int pos, int kb) {
    const uint32_t fb = sb + SM_BAR + 8 * (B_RA + kb);
    mbar_expect_tx(fb, UP && kb < NE ? 8192 : 16384);
    if (UP) {
        if (kb >= NE) tma2d(sb + kb * 16384, &maps.h, kb * 64, pos - 1024, fb);
        tma2d(sb + kb * 16384 + 8192, &maps.h, kb * 64, pos, fb);
    } else {
        tma2d(sb + kb * 16384, &maps.wqkv, pos, kb * 64, fb);
        tma2d(sb + kb * 16384 + 8192, &maps.wqkv, pos + 64, kb * 64, fb);
    }
}
template <bool UP>
__device__ __forceinline__ void rgemm_produce(uint32_t sb, const Maps& maps, int rpos, int spos) {
    int kb = 4;
#pragma unroll 1
    for (int i = 4; i < (UP ? 30 : 20); i++) {
        mbar_wait(sb + SM_BAR + 8 * (B_RE + 4 * UP + (i & 3)), ((i >> 2) - 1) & 1);
        rgemm_load_ring<UP>(sb, maps, spos, kb, i);
        if (i < 9) rgemm_load_res<UP>(sb, maps, rpos, i + 1);
        kb += (UP || i < 10) ? 1 : 2;
        if (kb == 10) { kb = 0; spos += (UP || i > 9) ? 64 : 1024; }
        if (UP && (i == 25 || i == 27 || i == 28)) mbar_arrive(sb + SM_BAR + 8 * (B_AF + (i == 25 ? 3 : i - 23)));
    }
    if (UP) {
        mbar_wait(sb + SM_BAR + 8 * (B_RE + 4 + 2), 0);
        mbar_arrive(sb + SM_BAR + 8 * (B_AF + 6));
    }
}
template <bool UP>
__device__ __forceinline__ void rgemm_phase(float (&acc)[64], uint32_t sb, uint32_t rpar, int p, int warp, int lane) {
    const uint32_t bar = sb + SM_BAR;
#pragma unroll
    for (int i = 0; i < 64; i++) acc[i] = 0.f;
    const bool solo = !UP && p;
    const int w1 = (warp >> 2) & 1, nrel = solo ? 2 : 1;
    if (p > 0) mbar_wait(bar + 8 * (solo && w1 ? B_SOLO : B_TURN + UP + p - 1), 0);
    else if (UP) mbar_wait(bar + 8 * B_HE, 0);
    const uint64_t da0 = mkdesc(sb + (UP ? 0 : SM_RING), 16, 1024, 1);
    const uint64_t db0 = mkdesc(sb + (UP ? SM_RING : 0), 8192, 1024, 1);
    int i = solo ? 10 + 5 * w1 : p * 10;
#pragma unroll 1
    for (int kb = 0; kb < 10; kb++) {
        const bool first = !solo || !(kb & 1);
        if (UP ? p == 0 && (w1 || kb >= NE) : true) mbar_wait(bar + 8 * (B_RA + kb), rpar);
        if (first) mbar_wait(bar + 8 * (B_RF + 4 * UP + (i & 3)), (i >> 2) & 1);
        if (kb == (solo ? 4 : 7) && (warp & 7) == 0 && lane == 0 && p < 2) mbar_arrive(bar + 8 * (solo ? B_SOLO : B_TURN + UP + p));
        const uint64_t da = da0 + (UP ? kb : i & 3) * 1024 + (solo ? kb & 1 : w1) * 512, db = db0 + (UP ? i & 3 : kb) * 1024;
        wg_fence();
#pragma unroll
        for (int kk = 0; kk < 4; kk++) {
            wgmma_ss_n128_tb(acc, da + kk * 2, db + kk * 128);
            if (kk == (UP ? 0 : 1)) {
                wg_commit();
                wg_wait<1>();
                if (kb > 0 && first && lane < nrel) mbar_arrive(bar + 8 * (B_RE + 4 * UP + ((i - 1) & 3)));
                wg_fence();
            }
        }
        wg_commit();
        if (!solo || (kb & 1)) i++;
    }
    wg_wait<0>();
    pin(acc);
    if (lane < nrel) mbar_arrive(bar + 8 * (B_RE + 4 * UP + ((i - 1) & 3)));
}

template <bool FUSED>
__global__ void __cluster_dims__(2, 1, 1) __launch_bounds__(NTHR, 1)
block_kernel(const __grid_constant__ Maps maps, const bf16* __restrict__ x, const bf16* __restrict__ wqkv,
             const bf16* __restrict__ wo, const bf16* __restrict__ wgate, const bf16* __restrict__ wup,
             const bf16* __restrict__ wdown, bf16* __restrict__ out, int phase_arg, uint32_t minus1) {
    const int phases = FUSED ? PH_ALL : phase_arg;
    if (threadIdx.x == 0) {
        l2_prefetch(wqkv + blockIdx.x * 1920, 3840);
        prefetch_map(&maps.wqkv);
        prefetch_map(&maps.x);
    }
    extern __shared__ __align__(1024) uint8_t smem[];
    const uint32_t sb = (uint32_t)__cvta_generic_to_shared(smem);
    const uint32_t bar = sb + SM_BAR;
    const int tid = threadIdx.x, warp = __shfl_sync(~0u, tid >> 5, 0), wg = warp >> 2, lane = tid & 31, g = lane >> 2, c = lane & 3;
    const int cl = blockIdx.x >> 1;
    const int b = 2 * ((cl & 7) * 8 + min(cl & 7, 2) + (cl >> 3)) + (blockIdx.x & 1);
    const bool main_cta = b < 128;
    const bool do_qkv = b < 120 && (phases & PH_QKV);
    const bool do_cs = b >= 120 && (phases & PH_PRE);
    const int qm = b < 96 ? ((b >> 4) & 1) * 4 + (b & 3) : b & 7, qn = b < 96 ? (b >> 5) * 4 + ((b >> 2) & 3) : b >> 3;
    const int head = b >> 2, qb = b & 3;
    const int ct = (b >> 1) % 5, tt = (b / 10) * 2 + (b & 1);
    const int oc = b % 10, ot = b / 10;
    const int mt = b >> 3, nt = b & 7;

    if (warp == 16) {
        if (elect_one()) {
#pragma unroll
            for (int i = 0; i < B_RA + 10; i++) mbar_init(bar + 8 * i, 1);
#pragma unroll
            for (int i = B_RE; i < B_RE + 4; i++) mbar_init(bar + 8 * i, 8);
            asm volatile("fence.proxy.async.shared::cta;" ::: "memory");
        }
        __syncwarp();
        asm volatile("bar.arrive 0, 640;" ::: "memory");
        if (do_qkv && elect_one()) {
#pragma unroll 1
            for (int i = 0; i < 5; i++) {
                rgemm_load_res<false>(sb, maps, qn * 128, i);
                if (i < 4) rgemm_load_ring<false>(sb, maps, qm * 128, i, i);
            }
            rgemm_produce<false>(sb, maps, qn * 128, qm * 128);
        }
        if (do_cs && elect_one()) {
#pragma unroll 1
            for (int kb = 0; kb < 5; kb++) {
                mbar_expect_tx(bar + 8 * (B_RA + kb), 40960);
                tma3d(sb + kb * 40960, &maps.wqkv5, 0, ((b & 1) * 5 + kb) * 64, ((b - 120) >> 1) * 5, bar + 8 * (B_RA + kb));
            }
#pragma unroll 1
            for (int i = 5; i < 10; i++) mbar_arrive(bar + 8 * (B_RA + i));
        }
        __syncwarp();
        bar_sync(8, 64);
    } else {
        if (warp == 17 && elect_one()) {
#pragma unroll
            for (int i = B_RA + 10; i < B_NUM; i++)
                if ((i < B_RE || i >= B_RE + 4) && (i < B_TF + 4 || i >= B_SOLO) && (i < B_TE + 4 || i >= B_PART1)) mbar_init(bar + 8 * i, i < B_TE ? 1 : i == B_PART1 ? 16 : i < B_STAT ? 8 : i == B_STAT ? 3 : i == B_STAT2 ? 3 : 16);
            asm volatile("fence.proxy.async.shared::cta;" ::: "memory");
        }
        __syncwarp();
        if (warp == 17) asm volatile("bar.arrive 8, 64;" ::: "memory");
        bar_sync(0, 640);
    }

    if (__builtin_expect(wg == 4, 1)) {
        asm volatile("setmaxnreg.dec.sync.aligned.u32 32;");
        const uint32_t epoch = __ldcg(g_cnt + C_EPOCH * 32);
        if (warp == 16) {
            if (main_cta && (phases & PH_ATT)) {
                const uint8_t* kv = g_qkv + (size_t)(32 + head) * 196608;
#pragma unroll 1
                for (int hf = 0; hf < 2; hf++) {
                    if (hf == 0) mbar_wait(bar + 8 * B_DEP1, 0);
                    else cnt_wait(lane < 6, C_QKV + 16 + (lane >> 1) * 5 + ((head * 20 + (lane & 1) * 19) >> 7), (epoch + 1) * 8);
                    if (elect_one()) {
                        fence_async_global();
                        if ((hf == 1 && do_qkv) || do_cs) mbar_wait(bar + 8 * B_FREE0, 0);
#pragma unroll 1
                        for (int ch = hf * 4; ch < hf * 4 + 4; ch++) {
                            if (ch == 1) mbar_wait(bar + 8 * B_AF, 0);
                            if ((ch == 1 || ch == 2) && do_qkv) mbar_wait(bar + 8 * (B_RE + ch - 1), 0);
                            mbar_expect_tx(bar + 8 * (B_AF + ch), 24576);
                            bulk_g2s(sb + ch * 24576, kv + ch * 24576, 24576, bar + 8 * (B_AF + ch));
                        }
                    }
                    __syncwarp();
                }
                float nn[3] = {0.f, 0.f, 0.f};
                const int np = (((head * 20) ^ (head * 20 + 19)) >> 7) ? 6 : 3;
#pragma unroll
                for (int i = 0; i < 6; i++) {
                    if (i < np) {
                        uint4 a;
#pragma unroll 1
                        for (int it = 0; it < 1000000; it++) {
                            asm volatile("ld.volatile.global.v4.u32 {%0, %1, %2, %3}, [%4];" : "=r"(a.x), "=r"(a.y), "=r"(a.z), "=r"(a.w) : "l"(g_nrm + (i * 32 + head) * 128 + lane * 4) : "memory");
                            if ((a.x ^ epoch) & (a.y ^ epoch) & (a.z ^ epoch) & (a.w ^ epoch) & 1) break;
                        }
                        __syncwarp();
                        nn[i % 3] += __uint_as_float(__reduce_max_sync(~0u, max(max(a.x, a.y), max(a.z, a.w))) & ~1u);
                    }
                }
                const float nq = nn[0], nk = nn[1], nv = nn[2];
                if (lane == 0) {
                    *(volatile uint32_t*)(smem + SM_VER) = (nq * nk <= 3300.f) && (nq <= 1e18f) && (nk <= 1e18f) && (nv <= 1e24f) && (nv >= 1e-24f);
                    mbar_arrive(bar + 8 * B_VER);
                }
                __syncwarp();
            }
            if (b < 130 && (phases & PH_OPJ)) {
                const int rb0 = (ot * 80) >> 7, rb1 = min((ot * 80 + 79) >> 7, 7);
                const bool busy = phases & (main_cta ? PH_ATT : PH_PRE);
                if (busy) mbar_wait(bar + 8 * B_PART1, 0);
                cnt_wait(rb0 + lane <= rb1, C_ATT + rb0 + lane, (epoch + 1) * 32);
                if (elect_one()) {
                    fence_async_global();
                    mbar_expect_tx(bar + 8 * B_OPE, 102400 + 10 * 8192);
#pragma unroll 1
                    for (int i = 0; i < 6; i++) {
                        tma2d(sb + wo_off(i), &maps.wo, oc * 64, i * 64, bar + 8 * B_OPE);
                        if (i == 3 && busy) mbar_wait(bar + 8 * B_HALF1, 0);
                        if (i < 5) tma3d(sb + i * 20480, &maps.o, i * 256, ot * 10, 0, bar + 8 * B_OPE);
                    }
                }
                __syncwarp();
                if (main_cta && (phases & PH_ATT)) bar_sync(0, 544);
                if (elect_one()) {
#pragma unroll 1
                    for (int i = 6; i < 10; i++) tma2d(sb + wo_off(i), &maps.wo, oc * 64, i * 64, bar + 8 * B_OPE);
                }
                __syncwarp();
                cnt_wait(rb0 + lane <= rb1, C_ATT + 8 + rb0 + lane, (epoch + 1) * 32);
                bar_sync(11, 160);
                if (elect_one()) {
                    fence_async_global();
#pragma unroll 1
                    for (int i = 0; i < 5; i++) {
                        mbar_expect_tx(bar + 8 * (B_RA + i), 20480);
                        tma3d(sb + i * 20480, &maps.o, i * 256, ot * 10, 1, bar + 8 * (B_RA + i));
                    }
#pragma unroll 1
                    for (int i = 5; i < 10; i++) mbar_arrive(bar + 8 * (B_RA + i));
                    if (main_cta && (phases & PH_UP)) {
                        if (busy) mbar_wait(bar + 8 * B_FREE1, 0);
                        rgemm_load_ring<true>(sb, maps, nt * 192, 0, 0);
                        rgemm_load_ring<true>(sb, maps, nt * 192, 1, 1);
                    }
                }
                __syncwarp();
            }
            if (main_cta && (phases & PH_UP)) {
                const int t0 = (mt * 64) / 80, t1 = (mt * 64 + 63) / 80;
                cnt_wait(t0 + lane <= t1, C_H + t0 + lane, (epoch + 1) * 10);
                if (phases & PH_OPJ) bar_sync(12, 160);
                if (elect_one()) {
                    fence_async_global();
                    mbar_expect_tx(bar + 8 * B_HE, NE * 8192);
#pragma unroll 1
                    for (int i = 0; i < NE; i++) {
                        if (i < 4 && (i >= 2 || !(phases & PH_OPJ))) rgemm_load_ring<true>(sb, maps, nt * 192, i, i);
                        tma2d(sb + i * 16384, &maps.h, i * 64, mt * 64, bar + 8 * B_HE);
                    }
                }
                __syncwarp();
                cnt_wait(t0 + lane <= t1, C_H + 13 + t0 + lane, (epoch + 1) * 10);
                if (elect_one()) {
                    fence_async_global();
#pragma unroll 1
                    for (int i = 0; i < 5; i++) rgemm_load_res<true>(sb, maps, 1024 + mt * 64, i);
                    if (phases & PH_OPJ) mbar_wait(bar + 8 * B_STG, 0);
                    rgemm_produce<true>(sb, maps, 1024 + mt * 64, nt * 192);
                }
                __syncwarp();
            } else if (b < 130 && (phases & PH_OPJ)) {
                bar_sync(12, 160);
            }
        } else {
            const int t = tid - 544;
            if (t == 0) {
                prefetch_map(&maps.wo); prefetch_map(&maps.o); prefetch_map(&maps.h); prefetch_map(&maps.wg);
                prefetch_map(&maps.wu); prefetch_map(&maps.act); prefetch_map(&maps.wd);
            }
            auto signal = [&](int cn) { bar_sync(warp - 17, 288); if (lane == 0) cnt_signal(cn); __syncwarp(); };
            if (do_qkv && warp >= 18) {
                const ulonglong2* sp = (const ulonglong2*)(g_stat1 + (warp - 18) * 1024 + qm * 128) + lane;
                ulonglong2 v, w;
                mbar_wait(bar + 8 * (B_RA + 5), 0);
#pragma unroll 1
                for (int it = 0; it < 1000000; it++) {
                    asm volatile("ld.volatile.global.v2.u64 {%0, %1}, [%2];" : "=l"(v.x), "=l"(v.y) : "l"(sp) : "memory");
                    asm volatile("ld.volatile.global.v2.u64 {%0, %1}, [%2];" : "=l"(w.x), "=l"(w.y) : "l"(sp + 32) : "memory");
                    if (((v.x ^ epoch) & (v.y ^ epoch) & (w.x ^ epoch) & (w.y ^ epoch) & 1) != 0) break;
                }
                v.x &= ~1ull; v.y &= ~1ull; w.x &= ~1ull; w.y &= ~1ull;
                ((ulonglong2*)(smem + SM_CS + 512))[(warp - 18) * 64 + lane] = v;
                ((ulonglong2*)(smem + SM_CS + 512))[(warp - 18) * 64 + 32 + lane] = w;
            }
            if (do_qkv) {
                if (warp == 17) {
                    const uint32_t* cp = g_cs1 + qn * 128 + lane * 4;
                    mbar_wait(bar + 8 * (B_RA + 5), 0);
                    uint4 v, w;
#pragma unroll 1
                    for (int it = 0; it < 1000000; it++) {
                        asm volatile("ld.volatile.global.v4.u32 {%0, %1, %2, %3}, [%4];" : "=r"(v.x), "=r"(v.y), "=r"(v.z), "=r"(v.w) : "l"(cp) : "memory");
                        asm volatile("ld.volatile.global.v4.u32 {%0, %1, %2, %3}, [%4];" : "=r"(w.x), "=r"(w.y), "=r"(w.z), "=r"(w.w) : "l"(cp + 1920) : "memory");
                        if ((v.x ^ epoch) & (v.y ^ epoch) & (v.z ^ epoch) & (v.w ^ epoch) & (w.x ^ epoch) & (w.y ^ epoch) & (w.z ^ epoch) & (w.w ^ epoch) & 1) break;
                    }
                    ((float4*)(smem + SM_CS))[lane] = make_float4(__uint_as_float(v.x & ~1u) + __uint_as_float(w.x & ~1u), __uint_as_float(v.y & ~1u) + __uint_as_float(w.y & ~1u),
                                                                  __uint_as_float(v.z & ~1u) + __uint_as_float(w.z & ~1u), __uint_as_float(v.w & ~1u) + __uint_as_float(w.w & ~1u));
                    if (lane == 0) *(volatile uint32_t*)(smem + SM_TAG) = ~epoch & 1u;
                }
                __syncwarp();
                if (lane == 0) mbar_arrive(bar + 8 * B_STAT);
            }
            if (warp == 17 && main_cta && (phases & PH_ATT)) {
                cnt_wait(lane < 6, C_QKV + (lane >> 1) * 5 + ((head * 20 + (lane & 1) * 19) >> 7), (epoch + 1) * 8);
                if (lane == 0) mbar_arrive(bar + 8 * B_DEP1);
            }
            if (warp >= 18) {
                if (do_qkv) signal(C_QKV + (warp - 18) * 16 + qn);
                if (main_cta && (phases & PH_ATT)) { signal(C_ATT + qb * 2 + warp - 18); signal(C_ATT + 8 + qb * 2 + warp - 18); }
                if (b < 130 && (phases & PH_OPJ)) {
                    bar_sync(warp - 4, 160);
                    if (lane == 0) cnt_signal(C_H + (warp - 18) * 13 + ot);
                    __syncwarp();
                    bar_sync(warp - 12, 160);
                    if (lane == 0) cnt_signal(C_ST2 + (warp - 18) * 13 + ot);
                    __syncwarp();
                }
            }
            if (main_cta && (phases & PH_UP)) {
                if (warp == 17) {
                    mbar_wait(bar + 8 * B_HE, 0);
                    cnt_wait(lane == 0, C_CS2, (epoch + 1) * 4);
#pragma unroll
                    for (int i = lane; i < 96; i += 32)
                        ((float4*)(smem + SM_CS))[i] = __ldcg((const float4*)(g_cs2 + (i >= 48 ? F_ - 192 : 0) + nt * 192) + i);
                } else {
                    const int t0 = (mt * 64) / 80, t1 = (mt * 64 + 63) / 80;
                    cnt_wait(t0 + lane <= t1, C_ST2 + (warp - 18) * 13 + t0 + lane, (epoch + 1) * 10);
                    float4 a = make_float4(0.f, 0.f, 0.f, 0.f);
#pragma unroll 5
                    for (int i = 0; i < 10; i++) {
                        const float4 u = __ldcg((const float4*)(g_part2 + i * S_ + (warp - 18) * 1024 + mt * 64) + lane);
                        a.x += u.x; a.y += u.y; a.z += u.z; a.w += u.w;
                    }
                    const float m0 = a.x * (1.f / D_), m1 = a.z * (1.f / D_);
                    ((float4*)(smem + SM_CS + 1536))[t - 32] = make_float4(rbf(m0), ln_rstd(fmaxf(a.y * (1.f / D_) - m0 * m0, 0.f)),
                                                                           rbf(m1), ln_rstd(fmaxf(a.w * (1.f / D_) - m1 * m1, 0.f)));
                }
                __syncwarp();
                if (lane == 0) mbar_arrive(bar + 8 * B_STAT2);
                if (warp >= 18) signal(C_ACT + (warp - 18) * 16 + mt);
                if (warp == 18) signal(C_ACT + 32 + mt);
            }
            if (warp != 18 && b < 130 && (phases & PH_DN)) {
                const int r0 = (tt * 80) >> 6, r1 = min((tt * 80 + 79) >> 6, 31);
#pragma unroll 1
                for (int p = warp == 17 ? 0 : 1; p < (warp == 17 ? 1 : 3); p++) {
                    if (main_cta && (phases & PH_UP)) mbar_wait(bar + 8 * (p == 2 ? B_FREE3 : B_TURN + 1 + p), 0);
                    cnt_wait(r0 + lane <= r1, C_ACT + p * 16 + ((r0 + lane) & 15), (epoch + 1) * 8);
                    if (lane == 0) mbar_arrive(bar + 8 * (B_AF + p));
                }
                if (warp == 17 && elect_one()) {
                    if (phases & PH_OPJ) mbar_wait(bar + 8 * B_STG, 0);
                    const uint32_t dpar = main_cta && (phases & PH_ATT);
                    int s = 0, ph = 1;
#pragma unroll 1
                    for (int j = 0; j < 24; j++) {
                        if (j < NDS) { if (main_cta && (phases & PH_UP)) mbar_wait(bar + 8 * (B_AF + 3 + j), dpar); }
                        else mbar_wait(bar + 8 * (B_TE + s), ph);
                        const int kb = (j & 7) * 3 + (j >> 3);
                        const uint32_t fb = bar + 8 * (B_TF + s), dst = sb + s * 26624;
                        mbar_expect_tx(fb, 26624);
                        tma2d(dst, &maps.wd, ct * 128, kb * 64, fb);
                        tma2d(dst + 8192, &maps.wd, ct * 128 + 64, kb * 64, fb);
                        if ((j & 7) == 0) { mbar_wait(bar + 8 * (B_AF + (j >> 3)), dpar); fence_async_global(); }
                        tma2d(dst + 16384, &maps.act, kb * 128, tt * 10, fb);
                        if (++s == NDS) { s = 0; ph ^= 1; }
                    }
                }
                __syncwarp();
            }
            if (warp == 19 && (phases & PH_DN) && lane == 0) {
                if (b < 130) mbar_wait(bar + 8 * B_AF, main_cta && (phases & PH_ATT));
                const uint32_t ticket = atomicAdd(g_cnt + C_DONE * 32, 1u);
                if (ticket + 1 == (epoch + 1) * NCTA) g_cnt[C_EPOCH * 32] = epoch + 1;
            }
        }
    } else {
        const int pair = wg >> 1;
        float* s_cs = (float*)(smem + SM_CS);
        const bool do_pre = main_cta && (phases & PH_PRE) && pair == 1;
        uint32_t epoch = 0;
        uint2 xv[2][5];
        if (do_pre) {
            epoch = __ldcg(g_cnt + C_EPOCH * 32);
            const uint2* xr = (const uint2*)(x + (size_t)(b * 16 + (warp & 7) * 2) * D_) + lane;
#pragma unroll
            for (int i = 0; i < 5; i++) { xv[0][i] = __ldg(xr + i * 32); xv[1][i] = __ldg(xr + i * 32 + 160); }
        }
        auto ln1_stats = [&]() {
#pragma unroll
            for (int r = 0; r < 2; r++) {
                float sm = 0.f;
#pragma unroll
                for (int i = 0; i < 5; i++) sm += (bf_lo(xv[r][i].x) + bf_hi(xv[r][i].x)) + (bf_lo(xv[r][i].y) + bf_hi(xv[r][i].y));
#pragma unroll
                for (int m = 16; m; m >>= 1) sm += __shfl_xor_sync(~0u, sm, m);
                const float mean = sm * (1.f / D_);
                float sq = 0.f;
#pragma unroll
                for (int i = 0; i < 5; i++) {
                    const float d0 = bf_lo(xv[r][i].x) - mean, d1 = bf_hi(xv[r][i].x) - mean, d2 = bf_lo(xv[r][i].y) - mean, d3 = bf_hi(xv[r][i].y) - mean;
                    sq += fmaf(d0, d0, d1 * d1) + fmaf(d2, d2, d3 * d3);
                }
#pragma unroll
                for (int m = 16; m; m >>= 1) sq += __shfl_xor_sync(~0u, sq, m);
                const uint32_t rs = __float_as_uint(ln_rstd(sq * (1.f / D_)));
                if (lane == 0)
                    asm volatile("st.volatile.global.u64 [%0], %1;" ::"l"(g_stat1 + b * 16 + (warp & 7) * 2 + r),
                                 "l"((uint64_t)((__float_as_uint(rbf(mean)) & ~1u) | (~epoch & 1u)) | ((uint64_t)rs << 32)) : "memory");
            }
        };
        if (__builtin_expect(do_cs, 0) && pair == 0) {
            float c0[4] = {0.f, 0.f, 0.f, 0.f}, c2[4] = {0.f, 0.f, 0.f, 0.f}, c4[4] = {0.f, 0.f, 0.f, 0.f};
            if (tid < 32) s_cs[lane] = __uint_as_float(0x3F803F80u);
            asm volatile("fence.proxy.async.shared::cta;" ::: "memory");
            bar_sync(3, 256);
            epoch = __ldcg(g_cnt + C_EPOCH * 32);
            const uint64_t dw = mkdesc(sb + wg * 8192, 0, 1024, 1), d1 = mkdesc(sb + SM_CS, 0, 0, 0);
#pragma unroll 1
            for (int kb = 0; kb < 5; kb++) {
                mbar_wait(bar + 8 * (B_RA + kb), 0);
                wg_fence();
#pragma unroll
                for (int kk = 0; kk < 4; kk++) {
                    wgmma_ss_n8_ta(c0, dw + kb * 2560 + kk * 128, d1);
                    wgmma_ss_n8_ta(c2, dw + kb * 2560 + 1024 + kk * 128, d1);
                    wgmma_ss_n8_ta(c4, dw + kb * 2560 + (4 - wg) * 512 + kk * 128, d1);
                }
                wg_commit();
            }
            wg_wait<0>();
            pin(c0); pin(c2); pin(c4);
            volatile uint32_t* cp = g_cs1 + (b & 1) * 1920 + ((b - 120) >> 1) * 320 + (warp & 3) * 16 + g + (c & 1) * 8;
            const float lo = (c & 1) ? c0[2] : c0[0], hi = (c & 1) ? c2[2] : c2[0];
            cp[wg * 64 + (c >> 1) * 128] = (__float_as_uint(c < 2 ? lo : hi) & ~1u) | (~epoch & 1u);
            if (wg == 0 && c < 2) cp[256] = (__float_as_uint(c ? c4[2] : c4[0]) & ~1u) | (~epoch & 1u);
            if (lane == 0) mbar_arrive(bar + 8 * B_FREE0);
        }
        if (do_pre) ln1_stats();

        if (do_qkv) {
            float acc[64];
            rgemm_phase<false>(acc, sb, 0, pair, warp, lane);
            if (pair == 1 && lane == 0) mbar_arrive(bar + 8 * B_FREE0);
            mbar_wait(bar + 8 * B_STAT, 0);
            const int kind = qn / 5, rt = pair * 8 + qm;
            uint32_t w0[20], w1[20];
            const int r5 = qn - kind * 5;
            if (r5 & 4) qkv_store<4>(acc, w0, w1, smem, kind, rt, warp, lane);
            else if (r5 & 2) {
                if (r5 & 1) qkv_store<3>(acc, w0, w1, smem, kind, rt, warp, lane);
                else qkv_store<2>(acc, w0, w1, smem, kind, rt, warp, lane);
            } else {
                if (r5 & 1) qkv_store<1>(acc, w0, w1, smem, kind, rt, warp, lane);
                else qkv_store<0>(acc, w0, w1, smem, kind, rt, warp, lane);
            }
            qkv_norms(w0, w1, smem, kind, r5, rt, warp, lane);
        }

        asm volatile("setmaxnreg.inc.sync.aligned.u32 112;");
        if (main_cta && (phases & PH_ATT)) {
            mbar_wait(bar + 8 * B_DEP1, 0);
            const uint64_t dK0 = mkdesc(sb, 128, 384, 0), dK1 = mkdesc(sb + 256, 0, 384, 0), dV = mkdesc(sb + 6144, 384, 128, 0);
            uint32_t qa[6];
            load_q(qa, head, (qb * 4 + wg) * 64 + (warp & 3) * 16, lane);
            bool fast = true;
#pragma unroll 1
            for (int blk = 0; blk < 2; blk++) {
                uint32_t q[8];
#pragma unroll
                for (int i = 0; i < 6; i++) q[i] = qa[i];
                q[6] = q[7] = 0;
                if (c == 3) q[4] = q[5] = 0;
                if (c == 2) { q[4] = q[5] = 0xC02543E0u; q[6] = 0x0000BBA8u; q[7] = 0x8000BBA8u; }
                pin(q);
                float o[12], s[64];
                uint32_t p[32];
#pragma unroll
                for (int i = 0; i < 12; i++) o[i] = 0.f;
                pin(o);
                uint64_t bk0 = dK0, bk1 = dK1, bv = dV;
#pragma unroll 1
                for (int jj = 0; jj < 8; jj++, bk0 += 1536, bk1 += 1536, bv += 1536) {
                    if (blk == 0) mbar_wait(bar + 8 * (B_AF + jj), 0);
                    else if (jj == 3 || jj == 5) { if (lane == 0) mbar_arrive(bar + 8 * (jj == 3 ? B_PART1 : B_HALF1)); }
                    else if (jj == 7 && (phases & PH_OPJ)) asm volatile("bar.arrive 0, 544;" ::: "memory");
#pragma unroll
                    for (int u = 0; u < 2; u++) {
                        wg_fence();
                        wgmma_rs_n128<0>(s, q[0], q[1], q[2], q[3], bk0 + u * 768);
                        wgmma_rs_n128<1>(s, q[4], q[5], q[6], q[7], bk1 + u * 768);
                        wg_commit();
                        wg_wait<0>();
                        pin(s);
                        softmax_pv<0, 8>(s, p, o, bv + u * 768, minus1);
                        softmax_pv<8, 16>(s, p, o, bv + u * 768, minus1);
                        wg_commit();
                        wg_wait<0>();
                        pin(o);
                    }
                }
                if (blk == 0) {
                    load_q(qa, head, (16 + qb * 4 + wg) * 64 + (warp & 3) * 16, lane);
                    mbar_wait(bar + 8 * B_VER, 0);
                    fast = __all_sync(~0u, *(volatile uint32_t*)(smem + SM_VER) != 0);
                    if (!fast) break;
                } else if (lane == 0) {
                    mbar_arrive(bar + 8 * B_FREE1);
                }
                attn_store(o, head, blk * 16 + qb * 4 + wg, warp, lane);
            }
            if (__builtin_expect(!fast, 0)) attention_general(sb, head, qb, phases & PH_OPJ);
        }
        if (__builtin_expect(!main_cta, 0) && (phases & PH_PRE)) {
            helper_pre((float*)(smem + 204800), b - 128, wo, wgate, wup, wdown);
            if (lane == 0) { mbar_arrive(bar + 8 * B_PART1); mbar_arrive(bar + 8 * B_HALF1); mbar_arrive(bar + 8 * B_FREE1); }
        }

        if (b < 130 && (phases & PH_OPJ)) {
            const uint32_t rpar = do_qkv || do_cs;
            if (!(wg & 1)) {
                float acc[40];
#pragma unroll
                for (int i = 0; i < 40; i++) acc[i] = 0.f;
                const uint64_t da0 = mkdesc(sb, 0, 1024, 1), db0 = mkdesc(sb, 128, 2048, 0);
                mbar_wait(bar + 8 * B_OPE, 0);
#pragma unroll 1
                for (int i = 0; i < 10; i++) {
                    if (pair && !(i & 1)) mbar_wait(bar + 8 * (B_RA + (i >> 1)), rpar);
                    const uint64_t da = da0 + (wo_off(i) >> 4), db = db0 + (i >> 1) * 1280 + (i & 1) * 64;
                    wg_fence();
#pragma unroll
                    for (int kk = 0; kk < 4; kk++) wgmma_ss_n80_tatb(acc, da + kk * 128, db + kk * 16);
                    wg_commit();
                }
                wg_wait<0>();
                pin(acc);
                asm volatile("bar.arrive %0, %1;" ::"r"(11 + pair), "r"(160) : "memory");
                if (pair) bar_sync(13, 256);
                const uint32_t a0 = sb + (((lane >> 4) << 3) + (lane & 7)) * 128 + (((2 * (warp & 3) + ((lane >> 3) & 1)) ^ (lane & 7)) << 4);
#pragma unroll
                for (int j = 0; j < 10; j += 2) {
                    uint32_t r0 = pack_bf16(acc[4 * j], acc[4 * j + 1]), r1 = pack_bf16(acc[4 * j + 2], acc[4 * j + 3]);
                    uint32_t r2 = pack_bf16(acc[4 * j + 4], acc[4 * j + 5]), r3 = pack_bf16(acc[4 * j + 6], acc[4 * j + 7]);
                    asm volatile("stmatrix.sync.aligned.m8n8.x4.trans.shared.b16 [%0], {%1, %2, %3, %4};" ::"r"(a0 + (j < 8 ? 155648 + j * 1024 : 143360)), "r"(r0), "r"(r1), "r"(r2), "r"(r3) : "memory");
                }
                asm volatile("bar.arrive %0, 256;" ::"r"(9 + pair) : "memory");
            } else {
                const int t = tid & 127, tok = pair * 1024 + ot * 80 + (t >> 3);
                const size_t goff = (size_t)tok * D_ + oc * 64 + (t & 7) * 8;
                const int nv = ot == 12 ? 4 : 5;
                uint4 rv[5];
#pragma unroll
                for (int i = 0; i < 5; i++) {
                    rv[i] = make_uint4(0, 0, 0, 0);
                    if (i < nv) rv[i] = __ldg((const uint4*)(x + goff + i * 16 * D_));
                }
                bar_sync(9 + pair, 256);
                const uint8_t* sp = smem + (t >> 3) * 128 + (((t & 7) ^ ((t >> 3) & 7)) << 4);
#pragma unroll
                for (int i = 0; i < 5; i++) {
                    if (i < nv) {
                        const uint4 v = *(const uint4*)(sp + (i < 4 ? 155648 + i * 2048 : 143360));
                        rv[i].x = add_bf16x2(v.x, rv[i].x);
                        rv[i].y = add_bf16x2(v.y, rv[i].y);
                        rv[i].z = add_bf16x2(v.z, rv[i].z);
                        rv[i].w = add_bf16x2(v.w, rv[i].w);
                        *(uint4*)(g_h + goff + i * 16 * D_) = rv[i];
                    }
                }
                asm volatile("bar.arrive %0, 160;" ::"r"(14 + pair) : "memory");
                if (!pair) asm volatile("bar.arrive 13, 256;" ::: "memory");
                if (lane == 0) mbar_arrive(bar + 8 * B_STG);
#pragma unroll 1
                for (int i = 0; i < nv; i++) {
                    const uint4 r = rv[0];
                    rv[0] = rv[1]; rv[1] = rv[2]; rv[2] = rv[3]; rv[3] = rv[4];
                    const float f[8] = {bf_lo(r.x), bf_hi(r.x), bf_lo(r.y), bf_hi(r.y), bf_lo(r.z), bf_hi(r.z), bf_lo(r.w), bf_hi(r.w)};
                    float sm = 0.f, sq = 0.f;
#pragma unroll
                    for (int q = 0; q < 8; q++) { sm += f[q]; sq = fmaf(f[q], f[q], sq); }
#pragma unroll
                    for (int m = 1; m < 8; m <<= 1) { sm += __shfl_xor_sync(~0u, sm, m); sq += __shfl_xor_sync(~0u, sq, m); }
                    if ((lane & 7) == 0) g_part2[oc * S_ + tok + 16 * i] = make_float2(sm, sq);
                }
                asm volatile("bar.arrive %0, 160;" ::"r"(6 + pair) : "memory");
            }
        }
        const size_t goff = (size_t)(tt * 80 + (tid >> 4)) * D_ + ct * 128 + (tid & 15) * 8;
        const int nvd = tt == 25 ? 3 : 5;
        uint4 rv[5];
#pragma unroll
        for (int i = 0; i < 5; i++) rv[i] = make_uint4(0, 0, 0, 0);
        auto load_resid = [&]() {
            mbar_wait(bar + 8 * B_AF, main_cta && (phases & PH_ATT));
#pragma unroll
            for (int i = 0; i < 5; i++)
                if (i < nvd) rv[i] = __ldcg((const uint4*)(g_h + goff + i * 16 * D_));
        };
        {
            if (main_cta && (phases & PH_UP)) {
                const uint32_t rpar = (do_qkv || do_cs ? 1 : 0) ^ ((phases & PH_OPJ) ? 1 : 0);
#pragma unroll 1
                for (int p = pair; p < 3; p += 2) {
                    float acc[64];
                    if (p == 2 && (phases & PH_DN)) load_resid();
                    rgemm_phase<true>(acc, sb, rpar, p, warp, lane);
                    if (p == 2 && lane == 0) mbar_arrive(bar + 8 * B_FREE3);
                    mbar_wait(bar + 8 * B_STAT2, 0);
                    const int rl = (warp & 7) * 16;
                    const float2* s_st = (const float2*)(smem + SM_CS + 1536);
                    const float2 st0 = s_st[rl + g], st1 = s_st[rl + g + 8];
                    uint8_t* ag = g_act + (size_t)((wg & 1) * 128 + mt * 8 + (warp & 3) * 2) * 24576 + (nt * 24 + p * 8) * 128 + lane * 4;
                    const float ka0 = 0.7978845608028654f * st0.y, kb0 = 0.044715f * ka0 * st0.y * st0.y, kc0 = 0.5f * st0.y * st0.y;
                    const float ka1 = 0.7978845608028654f * st1.y, kb1 = 0.044715f * ka1 * st1.y * st1.y, kc1 = 0.5f * st1.y * st1.y;
#pragma unroll
                    for (int j = 0; j < 8; j++) {
                        const float2 cg = *(const float2*)(s_cs + p * 64 + 8 * j + 2 * c), cu = *(const float2*)(s_cs + 192 + p * 64 + 8 * j + 2 * c);
                        float r[4];
#pragma unroll
                        for (int e = 0; e < 4; e++) {
                            const float mean = e < 2 ? st0.x : st1.x, kc = e < 2 ? kc0 : kc1;
                            const float G = fmaf(-mean, (e & 1) ? cg.y : cg.x, acc[4 * j + e]);
                            const float U = fmaf(-mean, (e & 1) ? cu.y : cu.x, acc[32 + 4 * j + e]);
                            const float z = G * fmaf(G * G, e < 2 ? kb0 : kb1, e < 2 ? ka0 : ka1);
                            float th;
                            asm("tanh.approx.f32 %0, %1;" : "=f"(th) : "f"(z));
                            r[e] = (G * U) * fmaf(th, kc, kc);
                        }
                        *(uint32_t*)(ag + j * 128) = pack_bf16(r[0], r[1]);
                        *(uint32_t*)(ag + j * 128 + 24576) = pack_bf16(r[2], r[3]);
                    }
                    publish(pair);
                }
            }
        }
        if (b < 130 && (phases & PH_DN)) {
            constexpr uint32_t stg = 6 * 26624;
            if (pair == 1) {
                float acc[40];
#pragma unroll
                for (int i = 0; i < 40; i++) acc[i] = 0.f;
                const uint64_t da0 = mkdesc(sb + (wg & 1) * 8192, 0, 1024, 1), db0 = mkdesc(sb + 16384, 128, 1024, 0);
                int s = 0, ph = 0;
                uint32_t pend = 0;
#pragma unroll 1
                for (int i = 0; i < 24; i++) {
                    mbar_wait(bar + 8 * (B_TF + s), ph);
                    wg_fence();
#pragma unroll
                    for (int kk = 0; kk < 4; kk++) {
                        wgmma_ss_n80_ta(acc, da0 + s * 1664 + kk * 128, db0 + s * 1664 + kk * 16);
                        if (kk == 0) {
                            wg_commit();
                            wg_wait<1>();
                            if (pend && lane == 0) mbar_arrive(pend);
                            wg_fence();
                        }
                    }
                    wg_commit();
                    pend = bar + 8 * (B_TE + s);
                    if (++s == NDS) { s = 0; ph ^= 1; }
                }
                wg_wait<0>();
                pin(acc);
                const uint32_t a0 = sb + stg + (((lane >> 4) << 3) + (lane & 7)) * 256 + (((2 * (warp & 7) + ((lane >> 3) & 1)) ^ (lane & 7)) << 4);
#pragma unroll
                for (int j = 0; j < 10; j += 2) {
                    uint32_t r0 = pack_bf16(acc[4 * j], acc[4 * j + 1]), r1 = pack_bf16(acc[4 * j + 2], acc[4 * j + 3]);
                    uint32_t r2 = pack_bf16(acc[4 * j + 4], acc[4 * j + 5]), r3 = pack_bf16(acc[4 * j + 6], acc[4 * j + 7]);
                    asm volatile("stmatrix.sync.aligned.m8n8.x4.trans.shared.b16 [%0], {%1, %2, %3, %4};" ::"r"(a0 + j * 2048), "r"(r0), "r"(r1), "r"(r2), "r"(r3) : "memory");
                }
                asm volatile("bar.arrive 5, 512;" ::: "memory");
            } else {
                if (!(main_cta && (phases & PH_UP))) load_resid();
                const uint8_t* sp = smem + stg + (tid >> 4) * 256 + (((tid & 15) ^ ((tid >> 4) & 7)) << 4);
#pragma unroll 1
                for (int live = 0; live < 2; live++) {
                    if (live) bar_sync(5, 512);
                    const int ns = live ? nvd : 0;
#pragma unroll
                    for (int i = 0; i < 5; i++) {
                        const uint4 v = *(const uint4*)(sp + i * 4096);
                        uint4 r;
                        r.x = add_bf16x2(v.x, rv[i].x);
                        r.y = add_bf16x2(v.y, rv[i].y);
                        r.z = add_bf16x2(v.z, rv[i].z);
                        r.w = add_bf16x2(v.w, rv[i].w);
                        asm volatile("{\n.reg .pred p;\nsetp.lt.s32 p, %5, %6;\n@p st.global.v4.u32 [%0], {%1, %2, %3, %4};\n}\n" ::"l"(out + goff + i * 16 * D_),
                                     "r"(r.x), "r"(r.y), "r"(r.z), "r"(r.w), "r"(i), "r"(ns) : "memory");
                    }
                }
            }
        }
    }
}

typedef CUresult (*EncodeFn)(CUtensorMap*, CUtensorMapDataType, cuuint32_t, void*, const cuuint64_t*, const cuuint64_t*,
                             const cuuint32_t*, const cuuint32_t*, CUtensorMapInterleave, CUtensorMapSwizzle,
                             CUtensorMapL2promotion, CUtensorMapFloatOOBfill);

static void enc2d(EncodeFn enc, CUtensorMap* m, CUtensorMapDataType dt, const void* p, uint64_t d0, uint64_t d1, uint64_t stride,
                  uint32_t b0, uint32_t b1, CUtensorMapSwizzle sw) {
    cuuint64_t dim[2] = {d0, d1}, str[1] = {stride};
    cuuint32_t box[2] = {b0, b1}, es[2] = {1, 1};
    enc(m, dt, 2, (void*)p, dim, str, box, es, CU_TENSOR_MAP_INTERLEAVE_NONE, sw, CU_TENSOR_MAP_L2_PROMOTION_L2_128B, CU_TENSOR_MAP_FLOAT_OOB_FILL_NONE);
}

extern "C" void kernel_launch(void* const* d_in, const int* in_sizes, int n_in, void* d_out, int out_size) {
    const bf16* x = (const bf16*)d_in[0];
    const bf16* wqkv = (const bf16*)d_in[1];
    const bf16* wo = (const bf16*)d_in[2];
    const bf16* wg = (const bf16*)d_in[4];
    const bf16* wu = (const bf16*)d_in[5];
    const bf16* wd = (const bf16*)d_in[6];

    EncodeFn enc = nullptr;
    cudaDriverEntryPointQueryResult qr;
    cudaGetDriverEntryPoint("cuTensorMapEncodeTiled", (void**)&enc, cudaEnableDefault, &qr);
    void *p_o, *p_h, *p_act;
    cudaGetSymbolAddress(&p_o, g_o);
    cudaGetSymbolAddress(&p_h, g_h);
    cudaGetSymbolAddress(&p_act, g_act);
    Maps m;
    const CUtensorMapDataType BF = CU_TENSOR_MAP_DATA_TYPE_BFLOAT16, U64 = CU_TENSOR_MAP_DATA_TYPE_UINT64;
    enc2d(enc, &m.x, BF, x, D_, S_, D_ * 2, 64, 64, CU_TENSOR_MAP_SWIZZLE_128B);
    enc2d(enc, &m.wqkv, BF, wqkv, 1920, D_, 1920 * 2, 64, 64, CU_TENSOR_MAP_SWIZZLE_128B);
    {
        cuuint64_t dim[3] = {64, D_, 30}, str[2] = {1920 * 2, 128};
        cuuint32_t box[3] = {64, 64, 5}, es[3] = {1, 1, 1};
        enc(&m.wqkv5, BF, 3, (void*)wqkv, dim, str, box, es, CU_TENSOR_MAP_INTERLEAVE_NONE, CU_TENSOR_MAP_SWIZZLE_128B,
            CU_TENSOR_MAP_L2_PROMOTION_L2_128B, CU_TENSOR_MAP_FLOAT_OOB_FILL_NONE);
    }
    enc2d(enc, &m.wo, BF, wo, D_, D_, D_ * 2, 64, 64, CU_TENSOR_MAP_SWIZZLE_128B);
    {
        cuuint64_t dim[3] = {1280, 128, 2}, str[2] = {10240, 128 * 10240};
        cuuint32_t box[3] = {256, 10, 1}, es[3] = {1, 1, 1};
        enc(&m.o, U64, 3, p_o, dim, str, box, es, CU_TENSOR_MAP_INTERLEAVE_NONE, CU_TENSOR_MAP_SWIZZLE_NONE,
            CU_TENSOR_MAP_L2_PROMOTION_L2_128B, CU_TENSOR_MAP_FLOAT_OOB_FILL_NONE);
    }
    enc2d(enc, &m.h, BF, p_h, D_, S_, D_ * 2, 64, 64, CU_TENSOR_MAP_SWIZZLE_128B);
    enc2d(enc, &m.wg, BF, wg, F_, D_, F_ * 2, 64, 64, CU_TENSOR_MAP_SWIZZLE_128B);
    enc2d(enc, &m.wu, BF, wu, F_, D_, F_ * 2, 64, 64, CU_TENSOR_MAP_SWIZZLE_128B);
    enc2d(enc, &m.act, U64, p_act, 3072, S_ / 8, 24576, 128, 10, CU_TENSOR_MAP_SWIZZLE_NONE);
    enc2d(enc, &m.wd, BF, wd, D_, F_, D_ * 2, 64, 64, CU_TENSOR_MAP_SWIZZLE_128B);

    cudaFuncSetAttribute(block_kernel<true>, cudaFuncAttributeMaxDynamicSharedMemorySize, SM_TOTAL);
    cudaFuncSetAttribute(block_kernel<false>, cudaFuncAttributeMaxDynamicSharedMemorySize, SM_TOTAL);
    cudaLaunchConfig_t cfg = {};
    cfg.gridDim = NCTA; cfg.blockDim = NTHR; cfg.dynamicSmemBytes = SM_TOTAL;
    cudaLaunchAttribute at;
    at.id = cudaLaunchAttributeClusterDimension; at.val.clusterDim.x = 2; at.val.clusterDim.y = 1; at.val.clusterDim.z = 1;
    cfg.attrs = &at; cfg.numAttrs = 1;
    int ncl = 0;
    cudaOccupancyMaxActiveClusters(&ncl, block_kernel<true>, &cfg);
    if (2 * ncl >= NCTA) {
        block_kernel<true><<<NCTA, NTHR, SM_TOTAL>>>(m, x, wqkv, wo, wg, wu, wd, (bf16*)d_out, PH_ALL, ~0u);
    } else {
        for (int ph = PH_PRE; ph <= PH_DN; ph <<= 1) block_kernel<false><<<NCTA, NTHR, SM_TOTAL>>>(m, x, wqkv, wo, wg, wu, wd, (bf16*)d_out, ph, ~0u);
    }
}
```
